```python
import torch

def _softmax(x, axis=-1):
    return torch.softmax(x, dim=axis)
def _gelu(x):
    return torch.nn.functional.gelu(x, approximate="tanh")
def _silu(x):
    return torch.nn.functional.silu(x)
def _sigmoid(x):
    return torch.sigmoid(x)
def _layernorm(x, axis=-1, eps=1e-5):
    m = x.mean(dim=axis, keepdim=True)
    v = x.var(dim=axis, keepdim=True, unbiased=False)
    return (x - m) / torch.sqrt(v + eps)
def _scatter_add(tgt, idx, src, axis=0):
    return tgt.clone().index_add_(axis, idx, src)
def _segment_sum(src, seg, n):
    out = torch.zeros((n,) + src.shape[1:], dtype=src.dtype)
    return out.index_add_(0, seg, src)
def _pad(x, pw):
    flat = tuple(v for pair in reversed(pw) for v in pair)
    return torch.nn.functional.pad(x, flat)

kernel_name = 'concat_heads__mha_block_cached__mha_block_cached__near_ridge'

def setup_inputs():

    _w = (lambda a: (lambda t: t.to(torch.bfloat16) if t.is_floating_point() else t)(torch.as_tensor(a)))
    def _A_setup():
        B, Sq, D = 8, 160, 1024
        H, Sk, Dh = 32, 1024, 128
        return {
            "x": _w((lambda *s: torch.randn(*s, dtype=torch.bfloat16) * 0.8)(B, Sq, D)),
            "k_cache": _w((lambda *s: torch.randn(*s, dtype=torch.bfloat16) * 0.8)(B, H, Sk, Dh)),
            "v_cache": _w((lambda *s: torch.randn(*s, dtype=torch.bfloat16) * 0.05)(B, H, Sk, Dh)),
            "wq": _w((lambda *s: torch.randn(*s, dtype=torch.bfloat16) * 0.8)(D, H * Dh) * (D ** -0.5)),
            "wo": _w((lambda *s: torch.randn(*s, dtype=torch.bfloat16) * 0.05)(H * Dh, D) * ((H * Dh) ** -0.5)),
        }
    _A_in = _A_setup()

    def _B_setup():
        B, Sq, D = 8, 160, 1024
        H, Sk, Dh = 32, 1024, 128
        return {
            "x": _w((lambda *s: torch.randn(*s, dtype=torch.bfloat16) * 0.8)(B, Sq, D)),
            "k_cache": _w((lambda *s: torch.randn(*s, dtype=torch.bfloat16) * 0.8)(B, H, Sk, Dh)),
            "v_cache": _w((lambda *s: torch.randn(*s, dtype=torch.bfloat16) * 0.05)(B, H, Sk, Dh)),
            "wq": _w((lambda *s: torch.randn(*s, dtype=torch.bfloat16) * 0.8)(D, H * Dh) * (D ** -0.5)),
            "wo": _w((lambda *s: torch.randn(*s, dtype=torch.bfloat16) * 0.05)(H * Dh, D) * ((H * Dh) ** -0.5)),
        }
    _B_in = _B_setup()

    return {
        "A_x": _A_in["x"],
        "A_k_cache": _A_in["k_cache"],
        "A_v_cache": _A_in["v_cache"],
        "A_wq": _A_in["wq"],
        "A_wo": _A_in["wo"],
        "B_x": _B_in["x"],
        "B_k_cache": _B_in["k_cache"],
        "B_v_cache": _B_in["v_cache"],
        "B_wq": _B_in["wq"],
        "B_wo": _B_in["wo"],
    }

def reference(A_x, A_k_cache, A_v_cache, A_wq, A_wo, B_x, B_k_cache, B_v_cache, B_wq, B_wo):
    def _A_ref(x, k_cache, v_cache, wq, wo):
        B, Sq, D = x.shape
        H, Dh = 32, 128
        q = (lambda x, *d: x.permute(*d))((x @ wq).reshape(B, Sq, H, Dh), 0, 2, 1, 3)
        scores = torch.einsum("bhqd,bhkd->bhqk", q, k_cache) * (Dh ** -0.5)
        p = _softmax(scores, axis=-1)
        o = torch.einsum("bhqk,bhkd->bhqd", p, v_cache)
        return (lambda x, *d: x.permute(*d))(o, 0, 2, 1, 3).reshape(B, Sq, H * Dh) @ wo

    def _B_ref(x, k_cache, v_cache, wq, wo):
        B, Sq, D = x.shape
        H, Dh = 32, 128
        q = (lambda x, *d: x.permute(*d))((x @ wq).reshape(B, Sq, H, Dh), 0, 2, 1, 3)
        scores = torch.einsum("bhqd,bhkd->bhqk", q, k_cache) * (Dh ** -0.5)
        p = _softmax(scores, axis=-1)
        o = torch.einsum("bhqk,bhkd->bhqd", p, v_cache)
        return (lambda x, *d: x.permute(*d))(o, 0, 2, 1, 3).reshape(B, Sq, H * Dh) @ wo

    a = _A_ref(A_x, A_k_cache, A_v_cache, A_wq, A_wo)
    b = _B_ref(B_x, B_k_cache, B_v_cache, B_wq, B_wo)
    return torch.concatenate([a, b], axis=-1)
```

```cpp
#include <cuda_runtime.h>
#include <cuda_bf16.h>
#include <cuda.h>
#include <stdint.h>

namespace {

constexpr int SQ = 160, DM = 1024, NH = 32, SK = 1024, DH = 128, NB = 8;
constexpr int A_SLOT = 16384, NA = 6;
constexpr int B_BLK = 20480;
constexpr int OFF_B = NA * A_SLOT;
constexpr int OFF_LSUM = OFF_B + 6 * B_BLK;
constexpr int OFF_LINV = OFF_LSUM + 8 * SQ * 4;
constexpr int OFF_BAR = OFF_LINV + SQ * 4;
constexpr int OFF_SINK = OFF_BAR + 640 + 1024;
constexpr int SMEM_BYTES = OFF_SINK + 2048 + 1024;
constexpr int BAR_FO = 37, BAR_FG = 41, BAR_BANK = 45, BAR_FS = 0, BAR_AEMPTY = 6, BAR_XFULL = 12, BAR_XEMPTY = 16, BAR_PFULL = 20, BAR_PEMPTY = 22,
              BAR_QFULL = 24, BAR_QEMPTY = 26, BAR_LREADY = 28, BAR_OSTORE = 29, BAR_PDONE = 30,
              BAR_REMPTY = 31;
constexpr float Q_SCALE = 0.08838834764831845f * 1.4426950408889634f;
constexpr uint32_t SPIN_LIMIT = 1u << 26;

#define KV_PROMO CU_TENSOR_MAP_L2_PROMOTION_L2_128B
#define W_PROMO CU_TENSOR_MAP_L2_PROMOTION_L2_128B

#define JSTAR 3
#define BANK_N 10
#define BANK_FIRST 3
#define BANK_DELAY 1500
#define BANK_PACE 260
#define PROBE_REP 2
#define W_EF 1

#define SM_A 5
#define SM_B 8

#define WAIT_HINT 0

#define SIDE_AWARE 1
#define LOCAL_SCRATCH 1

struct Maps {
  CUtensorMap x[2], wq[2], wo[2], k[2], v[2], kline[2], vline[2], out;
};
struct Ptrs {
  const __nv_bfloat16* k[2];
  const __nv_bfloat16* v[2];
};

constexpr int PAGE = 2 << 20, SLOTS_PER_PAGE = 25, SLOT_SPAN = 81920, PROBE_OFF = SLOTS_PER_PAGE * SLOT_SPAN;
constexpr uint32_t PART_MASK = (1u << 13) | (1u << 16) | (1u << 17) | (1u << 19);
__device__ uint4 g_scratch[22 * (PAGE / 16)];
__device__ uint32_t g_claim, g_claim_done;
__device__ __align__(16) uint32_t g_qflag[2 * NB * NH];
__device__ uint4 g_oflag[2 * NB * NH];

__device__ __forceinline__ uint32_t smem_u32(const void* p) { return (uint32_t)__cvta_generic_to_shared(p); }
__device__ __forceinline__ bool elect_one() {
  uint32_t p;
  asm volatile("{\n.reg .pred p;\nelect.sync _|p, 0xffffffff;\nselp.b32 %0, 1, 0, p;\n}\n" : "=r"(p));
  return p;
}
__device__ __forceinline__ void mbar_init(uint32_t bar, uint32_t cnt) {
  asm volatile("mbarrier.init.shared::cta.b64 [%0], %1;" ::"r"(bar), "r"(cnt));
}
__device__ __forceinline__ void mbar_arrive_expect_tx(uint32_t bar, uint32_t bytes) {
  asm volatile("mbarrier.arrive.expect_tx.shared::cta.b64 _, [%0], %1;" ::"r"(bar), "r"(bytes) : "memory");
}
__device__ __forceinline__ void mbar_expect_tx(uint32_t bar, uint32_t bytes) {
  asm volatile("mbarrier.expect_tx.relaxed.cta.shared::cta.b64 [%0], %1;" ::"r"(bar), "r"(bytes) : "memory");
}
__device__ __forceinline__ void mbar_arrive(uint32_t bar, uint32_t cnt) {
  asm volatile("mbarrier.arrive.shared::cta.b64 _, [%0], %1;" ::"r"(bar), "r"(cnt) : "memory");
}
__device__ __forceinline__ void mbar_arrive_if(uint32_t on, uint32_t bar, uint32_t cnt) {
  asm volatile("{\n.reg .pred p;\nsetp.ne.b32 p, %2, 0;\n@p mbarrier.arrive.shared::cta.b64 _, [%0], %1;\n}\n" ::"r"(bar),
               "r"(cnt), "r"(on) : "memory");
}
__device__ __forceinline__ void mbar_arrive_remote_if(uint32_t on, uint32_t bar, uint32_t cta, uint32_t cnt) {
  asm volatile(
      "{\n.reg .pred p;\n.reg .b32 ra;\nsetp.ne.b32 p, %3, 0;\nmapa.shared::cluster.u32 ra, %0, %1;\n"
      "@p mbarrier.arrive.shared::cluster.b64 _, [ra], %2;\n}\n" ::"r"(bar), "r"(cta), "r"(cnt), "r"(on) : "memory");
}
__device__ __forceinline__ void mbar_wait(uint32_t bar, uint32_t parity) {
  asm volatile(
      "{\n.reg .pred p;\n.reg .b32 n;\nmov.b32 n, 0;\n"
      "WAIT_%=:\n"
      "mbarrier.try_wait.parity.shared::cta.b64 p, [%0], %1;\n"
      "@p bra DONE_%=;\n"
      "add.u32 n, n, 1;\n"
      "setp.lt.u32 p, n, %2;\n"
      "@p bra WAIT_%=;\n"
      "trap;\n"
      "DONE_%=:\n}\n" ::"r"(bar), "r"(parity), "n"(SPIN_LIMIT), "n"(WAIT_HINT) : "memory");
}
__device__ __forceinline__ bool mbar_test(uint32_t bar, uint32_t parity) {
  uint32_t ok;
  asm volatile("{\n.reg .pred p;\nmbarrier.test_wait.parity.shared::cta.b64 p, [%1], %2;\nselp.b32 %0, 1, 0, p;\n}\n"
               : "=r"(ok) : "r"(bar), "r"(parity) : "memory");
  return ok;
}
__device__ __forceinline__ void tma_prefetch_2d(const CUtensorMap* m, int c0, int c1) {
  asm volatile("cp.async.bulk.prefetch.tensor.2d.L2.global [%0, {%1, %2}];" ::"l"(m), "r"(c0), "r"(c1) : "memory");
}
__device__ __forceinline__ void tma_2d(uint32_t dst, const CUtensorMap* m, int c0, int c1, uint32_t bar) {
  asm volatile(
      "cp.async.bulk.tensor.2d.shared::cluster.global.mbarrier::complete_tx::bytes [%0], [%1, {%3, %4}], [%2];" ::"r"(dst),
      "l"(m), "r"(bar), "r"(c0), "r"(c1) : "memory");
}
__device__ __forceinline__ void tma_2d_mc(uint32_t dst, const CUtensorMap* m, int c0, int c1, uint32_t bar, uint64_t pol) {
  asm volatile(
      "cp.async.bulk.tensor.2d.shared::cluster.global.mbarrier::complete_tx::bytes.multicast::cluster.L2::cache_hint"
      " [%0], [%1, {%3, %4}], [%2], %5, %6;" ::"r"(dst), "l"(m), "r"(bar), "r"(c0), "r"(c1), "h"((uint16_t)3), "l"(pol) : "memory");
}
__device__ __forceinline__ void tma_3d_hint(uint32_t dst, const CUtensorMap* m, int c1, uint32_t bar, uint64_t pol) {
  asm volatile(
      "cp.async.bulk.tensor.3d.shared::cluster.global.mbarrier::complete_tx::bytes.L2::cache_hint"
      " [%0], [%1, {%4, %3, %4}], [%2], %5;" ::"r"(dst), "l"(m), "r"(bar), "r"(c1), "r"(0), "l"(pol) : "memory");
}
__device__ __forceinline__ void tma_store_2d(const CUtensorMap* m, int c0, int c1, uint32_t src) {
  asm volatile("cp.async.bulk.tensor.2d.global.shared::cta.bulk_group [%0, {%2, %3}], [%1];" ::"l"(m), "r"(src), "r"(c0),
               "r"(c1) : "memory");
}
__device__ __forceinline__ void bulk_g2s(uint32_t dst, const void* src, uint32_t bytes, uint32_t bar) {
  asm volatile("cp.async.bulk.shared::cluster.global.mbarrier::complete_tx::bytes [%0], [%1], %2, [%3];" ::"r"(dst),
               "l"(src), "r"(bytes), "r"(bar) : "memory");
}
__device__ __forceinline__ void bulk_s2g(void* dst, uint32_t src, uint32_t bytes) {
  asm volatile("cp.async.bulk.global.shared::cta.bulk_group [%0], [%1], %2;" ::"l"(dst), "r"(src), "r"(bytes) : "memory");
}
__device__ __forceinline__ void bulk_prefetch(const void* src, uint32_t bytes, uint64_t pol) {
  asm volatile("cp.async.bulk.prefetch.L2.global.L2::cache_hint [%0], %1, %2;" ::"l"(src), "r"(bytes), "l"(pol) : "memory");
}
__device__ __forceinline__ void bulk_commit() { asm volatile("cp.async.bulk.commit_group;" ::: "memory"); }
template <int N> __device__ __forceinline__ void bulk_wait_read() { asm volatile("cp.async.bulk.wait_group.read %0;" ::"n"(N) : "memory"); }
template <int N> __device__ __forceinline__ void bulk_wait() { asm volatile("cp.async.bulk.wait_group %0;" ::"n"(N) : "memory"); }
__device__ __forceinline__ void fence_async_smem() { asm volatile("fence.proxy.async.shared::cta;" ::: "memory"); }
__device__ __forceinline__ void fence_async_global() { asm volatile("fence.proxy.async.global;" ::: "memory"); }
__device__ __forceinline__ void wgmma_fence() { asm volatile("wgmma.fence.sync.aligned;" ::: "memory"); }
__device__ __forceinline__ void wgmma_commit() { asm volatile("wgmma.commit_group.sync.aligned;" ::: "memory"); }
template <int N> __device__ __forceinline__ void wgmma_wait() { asm volatile("wgmma.wait_group.sync.aligned %0;" ::"n"(N) : "memory"); }
__device__ __forceinline__ void cluster_sync() {
  asm volatile("barrier.cluster.arrive.relaxed;\nbarrier.cluster.wait;" ::: "memory");
}
__device__ __forceinline__ uint64_t make_desc(uint32_t addr) {
  return (uint64_t)((addr & 0x3FFFF) >> 4) | ((uint64_t)1 << 16) | ((uint64_t)64 << 32) | ((uint64_t)1 << 62);
}
__device__ __forceinline__ uint64_t make_desc_n(uint32_t addr) {
  return (uint64_t)((addr & 0x3FFFF) >> 4) | ((uint64_t)256 << 16) | ((uint64_t)32 << 32) | ((uint64_t)2 << 62);
}
__device__ __forceinline__ float ex2(float x) {
  float y;
  asm volatile("ex2.approx.ftz.f32 %0, %1;" : "=f"(y) : "f"(x));
  return y;
}
__device__ __forceinline__ void sched_fence(uint32_t zero) {
  asm volatile("{\n.reg .pred p;\nsetp.eq.b32 p, %0, 0;\nFENCE_%=:\n@p bra.uni FDONE_%=;\nnanosleep.u32 1;\nbra.uni FENCE_%=;\nFDONE_%=:\n}\n" ::"r"(zero) : "memory");
}
__device__ __forceinline__ uint32_t pack_bf16(float lo, float hi) {
  uint32_t r;
  asm("cvt.rn.bf16x2.f32 %0, %1, %2;" : "=r"(r) : "f"(hi), "f"(lo));
  return r;
}
__device__ __forceinline__ void stsm_x4_t(uint32_t addr, uint32_t r0, uint32_t r1, uint32_t r2, uint32_t r3) {
  asm volatile("stmatrix.sync.aligned.m8n8.x4.trans.shared.b16 [%0], {%1, %2, %3, %4};" ::"r"(addr), "r"(r0), "r"(r1),
               "r"(r2), "r"(r3) : "memory");
}
__device__ __forceinline__ void stsm_x4(uint32_t addr, uint32_t r0, uint32_t r1, uint32_t r2, uint32_t r3) {
  asm volatile("stmatrix.sync.aligned.m8n8.x4.shared.b16 [%0], {%1, %2, %3, %4};" ::"r"(addr), "r"(r0), "r"(r1), "r"(r2),
               "r"(r3) : "memory");
}
__device__ __forceinline__ uint32_t wait_flag(const uint32_t* f) {
  uint32_t v, n = 0;
  while (true) {
    asm volatile("ld.acquire.gpu.global.u32 %0, [%1];" : "=r"(v) : "l"(f) : "memory");
    if (v) break;
    if (++n > (SPIN_LIMIT >> 2)) __trap();
    __nanosleep(32);
  }
  fence_async_global();
  return __shfl_sync(0xffffffffu, v, 0);
}

__device__ __forceinline__ uint8_t* scratch_base() {
  return reinterpret_cast<uint8_t*>((reinterpret_cast<uintptr_t>(g_scratch) + PAGE - 1) & ~(uintptr_t)(PAGE - 1));
}
__device__ __forceinline__ uint32_t slot_off(uint32_t slot) {
  return (slot / SLOTS_PER_PAGE) * PAGE + (slot % SLOTS_PER_PAGE) * SLOT_SPAN;
}
__device__ __forceinline__ uint32_t piece_off(uint32_t off, uint32_t sel) {
  return off + (((__popc(off & PART_MASK) ^ sel) & 1) << 12);
}
__device__ __forceinline__ uint32_t local_selector(uint8_t* page, uint32_t pair, uint32_t id) {
  const uint32_t off = PROBE_OFF + pair * 8192;
  uint8_t *p0 = page + piece_off(off, 0) + id * 32, *p1 = page + piece_off(off, 1) + id * 32;
  uint32_t t1, t2;
  asm volatile(
      "{\n.reg .b32 a, b;\n"
      "st.global.v4.u32 [%2], {0, 0, 0, 0};\nst.global.v4.u32 [%2+16], {0, 0, 0, 0};\n"
      "st.global.v4.u32 [%3], {0, 0, 0, 0};\nst.global.v4.u32 [%3+16], {0, 0, 0, 0};\n"
      "atom.relaxed.gpu.global.exch.b32 a, [%2], 1;\natom.relaxed.gpu.global.exch.b32 b, [%3], 1;\n"
      "{\n.reg .pred p;\nsetp.eq.u32 p, a, 0xffffffff;\n@p trap;\n}\n"
      "mov.u32 %0, %%clock;\n"
      "{\n.reg .pred p;\nsetp.eq.u32 p, b, 0xffffffff;\n@p trap;\n}\n"
      "mov.u32 %1, %%clock;\n}\n"
      : "=r"(t1), "=r"(t2) : "l"(p0), "l"(p1) : "memory");
  return t2 - t1 > 100 ? 0u : 1u;
}

template <int TA, int TB>
__device__ __forceinline__ void wgmma_160(float (&d)[80], uint64_t descA, uint64_t descB) {
  asm volatile(
      "wgmma.mma_async.sync.aligned.m64n160k16.f32.bf16.bf16 {"
      "%0, %1, %2, %3, %4, %5, %6, %7, %8, %9, %10, %11, %12, %13, %14, %15, "
      "%16, %17, %18, %19, %20, %21, %22, %23, %24, %25, %26, %27, %28, %29, %30, %31, "
      "%32, %33, %34, %35, %36, %37, %38, %39, %40, %41, %42, %43, %44, %45, %46, %47, "
      "%48, %49, %50, %51, %52, %53, %54, %55, %56, %57, %58, %59, %60, %61, %62, %63, "
      "%64, %65, %66, %67, %68, %69, %70, %71, %72, %73, %74, %75, %76, %77, %78, %79}, "
      "%80, %81, 1, 1, 1, %82, %83;\n"
      : "+f"(d[0]), "+f"(d[1]), "+f"(d[2]), "+f"(d[3]), "+f"(d[4]), "+f"(d[5]), "+f"(d[6]), "+f"(d[7]),
        "+f"(d[8]), "+f"(d[9]), "+f"(d[10]), "+f"(d[11]), "+f"(d[12]), "+f"(d[13]), "+f"(d[14]), "+f"(d[15]),
        "+f"(d[16]), "+f"(d[17]), "+f"(d[18]), "+f"(d[19]), "+f"(d[20]), "+f"(d[21]), "+f"(d[22]), "+f"(d[23]),
        "+f"(d[24]), "+f"(d[25]), "+f"(d[26]), "+f"(d[27]), "+f"(d[28]), "+f"(d[29]), "+f"(d[30]), "+f"(d[31]),
        "+f"(d[32]), "+f"(d[33]), "+f"(d[34]), "+f"(d[35]), "+f"(d[36]), "+f"(d[37]), "+f"(d[38]), "+f"(d[39]),
        "+f"(d[40]), "+f"(d[41]), "+f"(d[42]), "+f"(d[43]), "+f"(d[44]), "+f"(d[45]), "+f"(d[46]), "+f"(d[47]),
        "+f"(d[48]), "+f"(d[49]), "+f"(d[50]), "+f"(d[51]), "+f"(d[52]), "+f"(d[53]), "+f"(d[54]), "+f"(d[55]),
        "+f"(d[56]), "+f"(d[57]), "+f"(d[58]), "+f"(d[59]), "+f"(d[60]), "+f"(d[61]), "+f"(d[62]), "+f"(d[63]),
        "+f"(d[64]), "+f"(d[65]), "+f"(d[66]), "+f"(d[67]), "+f"(d[68]), "+f"(d[69]), "+f"(d[70]), "+f"(d[71]),
        "+f"(d[72]), "+f"(d[73]), "+f"(d[74]), "+f"(d[75]), "+f"(d[76]), "+f"(d[77]), "+f"(d[78]), "+f"(d[79])
      : "l"(descA), "l"(descB), "n"(TA), "n"(TB));
}
template <int TA, int TB>
__device__ __forceinline__ void wgmma_160_init(float (&d)[80], uint64_t descA, uint64_t descB) {
  asm volatile(
      "wgmma.mma_async.sync.aligned.m64n160k16.f32.bf16.bf16 {"
      "%0, %1, %2, %3, %4, %5, %6, %7, %8, %9, %10, %11, %12, %13, %14, %15, "
      "%16, %17, %18, %19, %20, %21, %22, %23, %24, %25, %26, %27, %28, %29, %30, %31, "
      "%32, %33, %34, %35, %36, %37, %38, %39, %40, %41, %42, %43, %44, %45, %46, %47, "
      "%48, %49, %50, %51, %52, %53, %54, %55, %56, %57, %58, %59, %60, %61, %62, %63, "
      "%64, %65, %66, %67, %68, %69, %70, %71, %72, %73, %74, %75, %76, %77, %78, %79}, "
      "%80, %81, 0, 1, 1, %82, %83;\n"
      : "=f"(d[0]), "=f"(d[1]), "=f"(d[2]), "=f"(d[3]), "=f"(d[4]), "=f"(d[5]), "=f"(d[6]), "=f"(d[7]),
        "=f"(d[8]), "=f"(d[9]), "=f"(d[10]), "=f"(d[11]), "=f"(d[12]), "=f"(d[13]), "=f"(d[14]), "=f"(d[15]),
        "=f"(d[16]), "=f"(d[17]), "=f"(d[18]), "=f"(d[19]), "=f"(d[20]), "=f"(d[21]), "=f"(d[22]), "=f"(d[23]),
        "=f"(d[24]), "=f"(d[25]), "=f"(d[26]), "=f"(d[27]), "=f"(d[28]), "=f"(d[29]), "=f"(d[30]), "=f"(d[31]),
        "=f"(d[32]), "=f"(d[33]), "=f"(d[34]), "=f"(d[35]), "=f"(d[36]), "=f"(d[37]), "=f"(d[38]), "=f"(d[39]),
        "=f"(d[40]), "=f"(d[41]), "=f"(d[42]), "=f"(d[43]), "=f"(d[44]), "=f"(d[45]), "=f"(d[46]), "=f"(d[47]),
        "=f"(d[48]), "=f"(d[49]), "=f"(d[50]), "=f"(d[51]), "=f"(d[52]), "=f"(d[53]), "=f"(d[54]), "=f"(d[55]),
        "=f"(d[56]), "=f"(d[57]), "=f"(d[58]), "=f"(d[59]), "=f"(d[60]), "=f"(d[61]), "=f"(d[62]), "=f"(d[63]),
        "=f"(d[64]), "=f"(d[65]), "=f"(d[66]), "=f"(d[67]), "=f"(d[68]), "=f"(d[69]), "=f"(d[70]), "=f"(d[71]),
        "=f"(d[72]), "=f"(d[73]), "=f"(d[74]), "=f"(d[75]), "=f"(d[76]), "=f"(d[77]), "=f"(d[78]), "=f"(d[79])
      : "l"(descA), "l"(descB), "n"(TA), "n"(TB));
}

enum { U_QP = 0, U_AT = 1, U_OP = 2, U_HQ = 3, U_END = 4 };
struct Sched {
  int g, idx;
  bool isG;
  int jstar;
  __device__ __forceinline__ static int jstar_of(int g, int i) { return i < 2 ? JSTAR : 0; }
  __device__ __forceinline__ static int a_head(int a, int item) {
    return item == 0 ? a : 2 * (4 + (item < 4 ? 4 * (item - 1) : 4 * (item - 4) + 2) + (a >> 1)) + (a & 1);
  }
  __device__ __forceinline__ static int op_head(int hidx) {
    const int batch = hidx >> 2, a = hidx & 3;
    return batch == 3 ? 4 + a : a_head(a, batch < 3 ? batch : batch - 1);
  }
  __device__ __forceinline__ int type(int u) const {
    if (isG) return u > 5 ? U_END : (u == 5 ? U_OP : (u == jstar ? U_HQ : (u == jstar + 1 ? U_AT : U_QP)));
    return u > 7 ? U_END : (u == 0 ? U_HQ : U_AT);
  }
  __device__ __forceinline__ int arg(int u) const {
    if (isG) return (u == jstar || u == jstar + 1) ? 4 + idx : 4 + 4 * (u > jstar ? u - 2 : u) + idx;
    return a_head(idx, u > 0 ? u - 1 : 0);
  }
  __device__ __forceinline__ int qbuf(int u) const { return isG ? 0 : ((u - 1) & 1); }
  __device__ __forceinline__ bool qloaded(int u) const { return !isG && u >= 2; }
  __device__ __forceinline__ int rot(int u) const { return (u == 0 || type(u - 1) == U_AT) ? 0 : 2; }
  __device__ __forceinline__ bool mc(int u) const { const int t = type(u); return t != U_AT && t != U_END; }
};

template <int V> struct Int { static constexpr int value = V; };

struct ARing {
  uint32_t slot, phase;
  __device__ __forceinline__ void adv(uint32_t n) {
    slot += n;
    if (slot >= NA) { slot -= NA; phase ^= 1; }
  }
};

__device__ __forceinline__ void release_a(uint32_t bars, uint32_t slot, bool next_mc, uint32_t peer, uint32_t cnt, uint32_t lead) {
  const uint32_t bar = bars + (BAR_AEMPTY + slot) * 8;
  mbar_arrive_if(lead, bar, cnt);
  mbar_arrive_remote_if(next_mc ? lead : 0u, bar + (BAR_REMPTY - BAR_AEMPTY) * 8, peer, cnt);
}

__device__ __forceinline__ void store_block_t(const float (&acc)[80], uint32_t blk, int warp, int lane) {
  const uint32_t addr = blk + ((lane & 7) + ((lane >> 4) << 3)) * 128 + (((2 * warp + ((lane >> 3) & 1)) ^ (lane & 7)) << 4);
#pragma unroll
  for (int j = 0; j < 10; j++) {
    stsm_x4_t(addr + j * 2048, pack_bf16(acc[8 * j], acc[8 * j + 1]), pack_bf16(acc[8 * j + 2], acc[8 * j + 3]),
              pack_bf16(acc[8 * j + 4], acc[8 * j + 5]), pack_bf16(acc[8 * j + 6], acc[8 * j + 7]));
  }
}
__device__ __forceinline__ uint32_t n_addr(uint32_t addr0, int j) { return (addr0 ^ ((j & 1) << 5)) + (j >> 1) * 4096; }
__device__ __forceinline__ void store_block_n(const float (&acc)[80], float scale, uint32_t addr0) {
#pragma unroll
  for (int j = 0; j < 10; j++) {
    stsm_x4(n_addr(addr0, j), pack_bf16(acc[8 * j] * scale, acc[8 * j + 1] * scale),
            pack_bf16(acc[8 * j + 2] * scale, acc[8 * j + 3] * scale),
            pack_bf16(acc[8 * j + 4] * scale, acc[8 * j + 5] * scale),
            pack_bf16(acc[8 * j + 6] * scale, acc[8 * j + 7] * scale));
  }
}

#define PROF(site, stmt) stmt
#define STAMP(idx)
#define TRACE(i)

__device__ __forceinline__ void slow_attention(uint8_t* qblk, const __nv_bfloat16* kp, const __nv_bfloat16* vp, int warp, int lane) {
  auto elem = [&](int d, int q) {
    return reinterpret_cast<__nv_bfloat16*>(qblk + (d >> 6) * B_BLK + (q >> 5) * 4096 + (d & 63) * 64 +
                                            ((((q >> 3) & 3) ^ ((d >> 1) & 3)) << 4) + (q & 7) * 2);
  };
#pragma unroll 1
  for (int q = warp; q < SQ; q += 4) {
    float m = -INFINITY, l = 0.f, o0 = 0.f, o1 = 0.f, o2 = 0.f, o3 = 0.f;
#pragma unroll 1
    for (int k0 = 0; k0 < SK; k0 += 32) {
      float s = 0.f;
      const uint32_t* kr = reinterpret_cast<const uint32_t*>(kp + (size_t)(k0 + lane) * DH);
#pragma unroll 1
      for (int d = 0; d < DH; d += 2) {
        const uint32_t kv = kr[d >> 1];
        s = fmaf(__bfloat162float(*elem(d, q)), __uint_as_float(kv << 16), s);
        s = fmaf(__bfloat162float(*elem(d + 1, q)), __uint_as_float(kv & 0xffff0000u), s);
      }
      float mn = s;
#pragma unroll
      for (int o = 16; o > 0; o >>= 1) mn = fmaxf(mn, __shfl_xor_sync(0xffffffffu, mn, o));
      mn = fmaxf(mn, m);
      float alpha = exp2f(m - mn), p = exp2f(s - mn);
      m = mn;
      l = l * alpha + p;
      o0 *= alpha; o1 *= alpha; o2 *= alpha; o3 *= alpha;
#pragma unroll 1
      for (int kk = 0; kk < 32; kk++) {
        float pk = __shfl_sync(0xffffffffu, p, kk);
        uint2 vv = *reinterpret_cast<const uint2*>(vp + (size_t)(k0 + kk) * DH + lane * 4);
        o0 = fmaf(pk, __uint_as_float(vv.x << 16), o0);
        o1 = fmaf(pk, __uint_as_float(vv.x & 0xffff0000u), o1);
        o2 = fmaf(pk, __uint_as_float(vv.y << 16), o2);
        o3 = fmaf(pk, __uint_as_float(vv.y & 0xffff0000u), o3);
      }
    }
#pragma unroll
    for (int o = 16; o > 0; o >>= 1) l += __shfl_xor_sync(0xffffffffu, l, o);
    float inv = 1.f / l;
    __syncwarp();
    *elem(4 * lane, q) = __float2bfloat16(o0 * inv);
    *elem(4 * lane + 1, q) = __float2bfloat16(o1 * inv);
    *elem(4 * lane + 2, q) = __float2bfloat16(o2 * inv);
    *elem(4 * lane + 3, q) = __float2bfloat16(o3 * inv);
  }
}

__global__ void __cluster_dims__(2, 1, 1) __launch_bounds__(512, 1)
mha2_kernel(const __grid_constant__ Maps maps, const __grid_constant__ Ptrs ptrs) {
  extern __shared__ uint8_t smem_raw[];
  uint8_t* smem = smem_raw + ((1024 - (smem_u32(smem_raw) & 1023)) & 1023);
  const uint32_t sbase = smem_u32(smem);
  const uint32_t bars = sbase + OFF_BAR;
  const int tid = threadIdx.x, lane = tid & 31;
  const int warp = __shfl_sync(0xffffffffu, (tid >> 5) & 3, 0);
  const uint32_t lead = lane == 0;
  const uint32_t zero = blockIdx.y;
  const int wg = __shfl_sync(0xffffffffu, tid >> 7, 0);
  const uint32_t rank = blockIdx.x & 1, peer = rank ^ 1;
  uint8_t* const scratch = scratch_base();
  volatile uint32_t* role_slot = reinterpret_cast<volatile uint32_t*>(smem + OFF_BAR + 504);

  if (tid == 32 && rank == 0) {
    const uint32_t ncl = gridDim.x >> 1;
    uint32_t side = 0;
#pragma unroll 1
    for (int i = 0; i < PROBE_REP; i++) side = local_selector(scratch, 5, blockIdx.x >> 1);
    const uint32_t old = atomicAdd(&g_claim, side ? 0x10000u : 1u);
    const uint32_t t = side ? old >> 16 : old & 0xffffu;
    uint32_t role = side * 32 + t;
    if (t >= 32) {
      uint32_t v, n = 0;
      while (true) {
        asm volatile("ld.relaxed.gpu.global.u32 %0, [%1];" : "=r"(v) : "l"(&g_claim) : "memory");
        if ((v >> 16) + (v & 0xffffu) >= ncl) break;
        if (++n > (SPIN_LIMIT >> 2)) __trap();
      }
      const uint32_t o = (side ? v & 0xffffu : v >> 16) + (t - 32);
      role = o < 32 ? (side ^ 1) * 32 + o : 64;
    }
    *role_slot = role;
    asm volatile("{\n.reg .b32 ra;\nmapa.shared::cluster.u32 ra, %0, 1;\nst.shared::cluster.u32 [ra], %1;\n}\n" ::"r"(bars + 504), "r"(role) : "memory");
    asm volatile("fence.acq_rel.cluster;" ::: "memory");
    if (atomicAdd(&g_claim_done, 1) == ncl - 1) {
      g_claim = 0;
      g_claim_done = 0;
    }
  }
  if (tid == 0) {
    for (int i = 0; i < NA; i++) {
      mbar_init(bars + (BAR_AEMPTY + i) * 8, 8);
      mbar_init(bars + (BAR_REMPTY + i) * 8, 8);
    }
    for (int i = 0; i < 4; i++) {
      mbar_init(bars + (BAR_XFULL + i) * 8, 1);
      mbar_init(bars + (BAR_FO + i) * 8, 1);
      mbar_init(bars + (BAR_FG + i) * 8, 1);
      mbar_init(bars + (BAR_FS + i) * 8, 1);
      mbar_init(bars + (BAR_XEMPTY + i) * 8, 12);
      mbar_init(bars + (BAR_PFULL + i) * 8, 4);
    }
    for (int i = 0; i < 2; i++) {
      mbar_init(bars + (BAR_QFULL + i) * 8, 8);
      mbar_init(bars + (BAR_QEMPTY + i) * 8, 1);
    }
    mbar_init(bars + BAR_PDONE * 8, 4);
    mbar_init(bars + BAR_BANK * 8, 1);
    mbar_init(bars + BAR_LREADY * 8, 8);
    mbar_init(bars + BAR_OSTORE * 8, 4);
    asm volatile("fence.mbarrier_init.release.cluster;" ::: "memory");
  }
  __syncthreads();
  cluster_sync();
  const int cl = __shfl_sync(0xffffffffu, *role_slot, 0);
  if (cl >= 64) return;
  Sched sc;
  sc.g = cl >> 3;
  sc.isG = (cl & 1) == 0;
  sc.idx = (cl & 7) >> 1;
  sc.jstar = Sched::jstar_of(sc.g, sc.idx);
  const int br = sc.g >> 2, b = (sc.g & 3) * 2 + rank;
  const int bh0 = (br * NB + b) * NH;
  const int cta = cl * 2 + rank;

  if (wg == 3) {
    asm volatile("setmaxnreg.dec.sync.aligned.u32 32;");
    if (warp == 0) {
      uint64_t pol;
      asm volatile("createpolicy.fractional.L2::evict_first.b64 %0, 1.0;" : "=l"(pol));
      ARing r{0, 1};
      uint32_t rm = 0x3F;
#pragma unroll 1
      for (int u = 0;; u++) {
        const int ty = sc.type(u);
        if (ty == U_END) break;
        const int arg = sc.arg(u);
        if (ty == U_AT) {
          const CUtensorMap *mk = &maps.k[br], *mv = &maps.v[br];
          const int row0 = (b * NH + arg) * SK;
#pragma unroll 1
          for (int j = -1; j < 16; j++) {
            if (j < 15) {
              const uint32_t full = bars + (BAR_FS + ((j + 1) & 3)) * 8;
              PROF(0, mbar_wait(bars + (BAR_AEMPTY + r.slot) * 8, r.phase));
              if (elect_one()) {
                mbar_arrive_expect_tx(full, A_SLOT);
                tma_3d_hint(sbase + r.slot * A_SLOT, mk, row0 + (j + 1) * 64, full, pol);
              }
              r.adv(1);
            }
            if (j >= 0) {
              const uint32_t full = bars + (BAR_FO + (j & 3)) * 8;
              PROF(0, mbar_wait(bars + (BAR_AEMPTY + r.slot) * 8, r.phase));
              if (elect_one()) {
                mbar_arrive_expect_tx(full, A_SLOT);
                tma_3d_hint(sbase + r.slot * A_SLOT, mv, row0 + j * 64, full, pol);
              }
              r.adv(1);
            }
          }
        } else {
          const CUtensorMap* mw = ty == U_OP ? &maps.wo[br] : &maps.wq[br];
          const int col = (ty == U_HQ ? arg * 128 : (ty == U_QP ? arg : sc.idx) * 256) + rank * 64;
          const int n = ty == U_OP ? 64 : 16;
          int row = 0;
#pragma unroll 1
          for (int s = 0; s < n; s++) {
            if (ty == U_OP && (s & 1) == 0) row = Sched::op_head(s >> 1) * DH;
#pragma unroll 1
            for (int i = ty == U_HQ ? 1 : 0; i < 2; i++) {
              const uint32_t full = bars + ((i == 0 ? BAR_FO : (ty == U_HQ && !(s & 4)) ? BAR_FS : BAR_FG) + (s & 3)) * 8;
              PROF(0, mbar_wait(bars + (BAR_AEMPTY + r.slot) * 8, r.phase));
              PROF(1, mbar_wait(bars + (BAR_REMPTY + r.slot) * 8, (rm >> r.slot) & 1));
              rm ^= 1u << r.slot;
              if (elect_one()) {
                mbar_arrive_expect_tx(full, A_SLOT);
                tma_2d_mc(sbase + r.slot * A_SLOT + rank * 8192, mw, col + (i ^ 1) * 128, row, full, pol);
              }
              r.adv(1);
            }
            row += 64;
          }
        }
      }
    } else if (warp == 1) {
      uint32_t qm = 0, pdph = 0;
#pragma unroll 1
      for (int u = 0;; u++) {
        const int ty = sc.type(u);
        if (ty == U_END) break;
        if (ty == U_AT) {
          if (sc.qloaded(u)) {
            const int slot = bh0 + sc.arg(u), qb = sc.qbuf(u);
            uint32_t sel;
            PROF(2, sel = wait_flag(&g_qflag[slot]));
            const uint32_t full = bars + (BAR_QFULL + qb) * 8;
            mbar_wait(bars + (BAR_QEMPTY + qb) * 8, ((qm >> qb) & 1) ^ 1);
            mbar_wait(bars + BAR_XEMPTY * 8, 1);
            mbar_wait(bars + (BAR_XEMPTY + 1) * 8, 1);
            if (elect_one()) {
              g_qflag[slot] = 0;
              mbar_expect_tx(full, 2 * B_BLK);
              mbar_arrive(full, 8);
              const uint32_t off = slot_off(slot);
#pragma unroll 1
              for (int i = 0; i < 10; i++)
                bulk_g2s(sbase + OFF_B + 2 * qb * B_BLK + i * 4096, scratch + piece_off(off + i * 8192, sel), 4096, full);
            }
            qm ^= 1u << qb;
          }
        } else {
          const int n = ty == U_OP ? 64 : 16, rot = sc.rot(u);
          const bool prev_at = u > 0 && sc.type(u - 1) == U_AT;
          uint32_t off = 0, sel = 0;
#pragma unroll 1
          for (int s = 0; s < n; s++) {
            const int x = (s + rot) & 3;
            if (ty == U_OP && (s & 1) == 0) {
              const int slot = bh0 + Sched::op_head(s >> 1);
              off = slot_off(slot);
              uint32_t* f = reinterpret_cast<uint32_t*>(&g_oflag[slot]) + sc.idx;
              PROF(2, sel = wait_flag(f));
              if (elect_one()) *f = 0;
            }
            if (s < 4) {
              if (x == 0) PROF(4, mbar_wait(bars + (BAR_QEMPTY + 1) * 8, ((qm >> 1) & 1) ^ 1));
              if (x == 2 && prev_at) { mbar_wait(bars + BAR_PDONE * 8, pdph); pdph ^= 1; }
            }
            const uint32_t full = bars + (BAR_XFULL + x) * 8, dst = sbase + OFF_B + (2 + x) * B_BLK;
            PROF(3, mbar_wait(bars + (BAR_XEMPTY + x) * 8, ((s >> 2) & 1) ^ 1));
            if (elect_one()) {
              mbar_arrive_expect_tx(full, B_BLK);
              if (ty != U_OP) {
                tma_2d(dst, &maps.x[br], s * 64, b * SQ, full);
              } else {
#pragma unroll
                for (int i = 0; i < 5; i++)
                  bulk_g2s(dst + i * 4096, scratch + piece_off(off + ((s & 1) * 5 + i) * 8192, sel), 4096, full);
              }
            }
          }
          qm ^= ty == U_HQ ? 1 : 3;
        }
      }
    } else if (warp == 2 && lane == 0) {
      uint32_t qm = 0, oph = 0;
      const uint32_t page0 = bh0 / SLOTS_PER_PAGE;
      uint32_t selmask = 0;
#pragma unroll 1
      for (int i = 0; i < 9; i++) selmask += local_selector(scratch + min(page0 + i / 3, 20u) * PAGE, i % 3, cta) << (2 * (i / 3));
      auto store_slot = [&](uint32_t slot, uint32_t src) {
        const uint32_t sel = (selmask >> (2 * (slot / SLOTS_PER_PAGE - page0) + 1)) & 1, off = slot_off(slot);
#pragma unroll 1
        for (int i = 0; i < 10; i++) bulk_s2g(scratch + piece_off(off + i * 8192, sel), src + i * 4096, 4096);
        bulk_commit();
        return 2 + sel;
      };
#pragma unroll 1
      for (int u = 0;; u++) {
        const int ty = sc.type(u);
        if (ty == U_END) break;
        if (ty == U_AT) {
          const int slot = bh0 + sc.arg(u), qb = sc.qbuf(u);
          if (sc.qloaded(u)) qm ^= 1u << qb;
          mbar_wait(bars + BAR_OSTORE * 8, oph);
          oph ^= 1;
          const uint32_t fv = store_slot(slot, sbase + OFF_B + 2 * qb * B_BLK);
          bulk_wait_read<0>();
          mbar_arrive(bars + (BAR_QEMPTY + qb) * 8, 1);
          bulk_wait<0>();
          fence_async_global();
          asm volatile("fence.release.gpu;" ::: "memory");
          asm volatile("st.relaxed.gpu.global.v4.u32 [%0], {%1, %1, %1, %1};" ::"l"(&g_oflag[slot]), "r"(fv) : "memory");
        } else if (ty == U_HQ) {
          qm ^= 1;
        } else if (ty == U_QP) {
          const int slot = bh0 + 2 * sc.arg(u);
          uint32_t fv = 0;
#pragma unroll 1
          for (int h = 1; h >= 0; h--) {
            mbar_wait(bars + (BAR_QFULL + h) * 8, (qm >> h) & 1);
            fv |= store_slot(slot + h, sbase + OFF_B + 2 * h * B_BLK) << (2 * h);
            bulk_wait_read<0>();
            mbar_arrive(bars + (BAR_QEMPTY + h) * 8, 1);
          }
          bulk_wait<0>();
          fence_async_global();
          asm volatile("fence.release.gpu;" ::: "memory");
          asm volatile("st.relaxed.gpu.global.v2.u32 [%0], {%1, %2};" ::"l"(&g_qflag[slot]), "r"(fv & 3), "r"(fv >> 2) : "memory");
          qm ^= 3;
        } else {
#pragma unroll 1
          for (int i = 0; i < 4; i++) {
            mbar_wait(bars + (BAR_QFULL + (i >> 1)) * 8, (qm >> (i >> 1)) & 1);
            tma_store_2d(&maps.out, br * DM + sc.idx * 256 + i * 64, b * SQ, sbase + OFF_B + i * B_BLK);
          }
          bulk_commit();
          bulk_wait<0>();
        }
      }
    }
    if (warp == 3 && sc.isG && sc.jstar == 0 && BANK_N > 0) {
      const int line0 = (b * NH + 4 + sc.idx) * SK * 2;
      const uint32_t bar = bars + BAR_BANK * 8;
      if (elect_one()) mbar_arrive_expect_tx(bar, BANK_N * 4096);
      __nanosleep(BANK_DELAY);
#pragma unroll 1
      for (int i = 0; i < 2 * BANK_N; i++) {
        const int tile = BANK_FIRST + (i >> 1) * (16 - BANK_FIRST) / (BANK_N > 0 ? BANK_N : 1);
        if (elect_one()) tma_2d(sbase + OFF_SINK, (i & 1) ? &maps.vline[br] : &maps.kline[br], 0, line0 + tile * 128, bar);
        __nanosleep(BANK_PACE);
      }
      mbar_wait(bar, 0);
    }
    __syncwarp();
    cluster_sync();
  } else if (wg == 0) {
    asm volatile("setmaxnreg.inc.sync.aligned.u32 192;");
    ARing r{0, 0};
    uint32_t lph = 0;
    const uint32_t st_off = (16 * warp + (lane & 15)) * 64 + (((lane >> 4) ^ ((lane & 7) >> 1)) << 4);
#pragma unroll 1
    for (int u = 0;; u++) {
      const int ty = sc.type(u);
      if (ty == U_END) break;
      const bool mc_next = sc.mc(u + 1);
      TRACE(u);
      if (ty == U_HQ) {
        r.adv(4);
        TRACE(8 + u);
        continue;
      }
      const bool at = ty == U_AT;
      const int n = ty == U_OP ? 64 : 16;
      const int rot = at ? 0 : sc.rot(u);
      float acc0[80], acc1[80];
      if (at) r.adv(2);
      const uint32_t bfull = bars + (at ? BAR_PFULL - 2 : BAR_XFULL) * 8, bempty = bars + (at ? BAR_PEMPTY - 2 : BAR_XEMPTY) * 8;
      uint32_t x = at ? 2 : rot;
      auto mainloop = [&](auto tb) {
        constexpr int TB = decltype(tb)::value;
        constexpr int KB = TB ? 64 : 2;
        PROF(5, mbar_wait(bfull + x * 8, 0));
        PROF(6, mbar_wait(bars + BAR_FO * 8, 0));
        {
          const uint32_t baddr = sbase + OFF_B + (2 + x) * B_BLK;
          const uint64_t da = make_desc(sbase + r.slot * A_SLOT), db = TB ? make_desc_n(baddr) : make_desc(baddr);
          wgmma_fence();
          wgmma_160_init<1, TB>(acc0, da, db);
          wgmma_160_init<1, TB>(acc1, da + 512, db);
#pragma unroll
          for (int kk = 1; kk < 4; kk++) {
            wgmma_160<1, TB>(acc0, da + kk * 128, db + kk * KB);
            wgmma_160<1, TB>(acc1, da + 512 + kk * 128, db + kk * KB);
          }
          wgmma_commit();
        }
#pragma unroll 1
        for (int s = 1; s < n; s++) {
          const uint32_t pslot = r.slot, px = x;
          r.adv((at && s == 15) ? 1 : 2);
          x = at ? 2 + (s & 1) : (s + rot) & 3;
          const uint32_t bpar = (at ? s >> 1 : s >> 2) & 1;
          const uint32_t afull = bars + (BAR_FO + (s & 3)) * 8;
          const bool okb = mbar_test(bfull + x * 8, bpar), oka = mbar_test(afull, (s >> 2) & 1);
          const uint32_t baddr = sbase + OFF_B + (2 + x) * B_BLK;
          const uint64_t da = make_desc(sbase + r.slot * A_SLOT), db = TB ? make_desc_n(baddr) : make_desc(baddr);
          STAMP(128 + (s & 15) * 4);
          PROF(9, wgmma_wait<0>());
          STAMP(128 + (s & 15) * 4 + 1);
          mbar_arrive_if(lead, bempty + px * 8, 1);
          release_a(bars, pslot, (at ? 2 * s : 2 * s - 2) + NA < 2 * n ? !at : mc_next, peer, 2, lead);
          if (!okb) PROF(7, mbar_wait(bfull + x * 8, bpar));
          if (!oka) PROF(8, mbar_wait(afull, (s >> 2) & 1));
          STAMP(128 + (s & 15) * 4 + 2);
          wgmma_fence();
#pragma unroll
          for (int kk = 0; kk < 4; kk++) {
            wgmma_160<1, TB>(acc0, da + kk * 128, db + kk * KB);
            wgmma_160<1, TB>(acc1, da + 512 + kk * 128, db + kk * KB);
          }
          wgmma_commit();
        }
      };
      if (ty == U_QP) {
        mainloop(Int<0>{});
        wgmma_wait<0>();
        mbar_arrive_if(lead, bempty + x * 8, 1);
        release_a(bars, r.slot, mc_next, peer, 2, lead);
        r.adv(2);
        mbar_wait(bars + BAR_XEMPTY * 8, 1);
        store_block_n(acc0, Q_SCALE, sbase + OFF_B + 2 * B_BLK + st_off);
        mbar_wait(bars + (BAR_XEMPTY + 1) * 8, 1);
        store_block_n(acc1, Q_SCALE, sbase + OFF_B + 3 * B_BLK + st_off);
        fence_async_smem();
        __syncwarp();
        mbar_arrive_if(lead, bars + (BAR_QFULL + 1) * 8, 2);
      } else {
        mainloop(Int<1>{});
        if (at) {
          const uint32_t blk = 2 * sc.qbuf(u);
          PROF(10, mbar_wait(bars + BAR_LREADY * 8, lph));
          lph ^= 1;
          float* linv = reinterpret_cast<float*>(smem + OFF_LINV);
          bool bad = false;
          if (lane < 20) {
            const int qp = warp * 20 + lane;
            const float2* lsum = reinterpret_cast<const float2*>(smem + OFF_LSUM) + qp;
            float2 l = lsum[0];
#pragma unroll
            for (int w = 1; w < 8; w++) {
              const float2 v = lsum[w * (SQ / 2)];
              l.x += v.x;
              l.y += v.y;
            }
            bad = !(l.x >= 9.094947e-13f && l.x <= 1.0995116e12f && l.y >= 9.094947e-13f && l.y <= 1.0995116e12f);
            *reinterpret_cast<float2*>(linv + (qp & 3) * 40 + (qp >> 2) * 2) = make_float2(__fdividef(1.f, l.x), __fdividef(1.f, l.y));
          }
          uint32_t anybad;
          asm volatile("{\n.reg .pred p, q;\nsetp.ne.b32 p, %1, 0;\nbar.red.or.pred q, 1, 128, p;\nselp.b32 %0, 1, 0, q;\n}\n"
                       : "=r"(anybad) : "r"((uint32_t)bad) : "memory");
          const float4* lv = reinterpret_cast<const float4*>(linv + (lane & 3) * 40);
          float4 iv[10];
          iv[0] = lv[0];
          iv[1] = lv[1];
          STAMP(128);
          wgmma_wait<0>();
          STAMP(129);
          mbar_arrive_if(lead, bempty + x * 8, 1);
          mbar_arrive_if(lead, bars + BAR_PDONE * 8, 1);
          release_a(bars, r.slot, mc_next, peer, 2, lead);
          r.adv(1);
          if (!__any_sync(0xffffffffu, anybad)) {
            const uint32_t addr = sbase + OFF_B + blk * B_BLK + st_off;
#pragma unroll
            for (int j = 0; j < 10; j++) {
              if (j == 1) {
#pragma unroll
                for (int i = 2; i < 5; i++) iv[i] = lv[i];
              }
              if (j == 2) {
#pragma unroll
                for (int i = 5; i < 10; i++) iv[i] = lv[i];
              }
              stsm_x4(n_addr(addr, j), pack_bf16(acc0[8 * j] * iv[j].x, acc0[8 * j + 1] * iv[j].y),
                      pack_bf16(acc0[8 * j + 2] * iv[j].x, acc0[8 * j + 3] * iv[j].y),
                      pack_bf16(acc0[8 * j + 4] * iv[j].z, acc0[8 * j + 5] * iv[j].w),
                      pack_bf16(acc0[8 * j + 6] * iv[j].z, acc0[8 * j + 7] * iv[j].w));
              stsm_x4(n_addr(addr, j) + B_BLK, pack_bf16(acc1[8 * j] * iv[j].x, acc1[8 * j + 1] * iv[j].y),
                      pack_bf16(acc1[8 * j + 2] * iv[j].x, acc1[8 * j + 3] * iv[j].y),
                      pack_bf16(acc1[8 * j + 4] * iv[j].z, acc1[8 * j + 5] * iv[j].w),
                      pack_bf16(acc1[8 * j + 6] * iv[j].z, acc1[8 * j + 7] * iv[j].w));
            }
          } else {
            const size_t off = (size_t)(b * NH + sc.arg(u)) * SK * DH;
            slow_attention(smem + OFF_B + blk * B_BLK, ptrs.k[br] + off, ptrs.v[br] + off, warp, lane);
          }
          fence_async_smem();
          __syncwarp();
          mbar_arrive_if(lead, bars + BAR_OSTORE * 8, 1);
          STAMP(130);
        } else {
          wgmma_wait<0>();
          mbar_arrive_if(lead, bempty + x * 8, 1);
          mbar_wait(bars + BAR_XEMPTY * 8, 1);
          store_block_t(acc0, sbase + OFF_B + 2 * B_BLK, warp, lane);
          mbar_wait(bars + (BAR_XEMPTY + 1) * 8, 1);
          store_block_t(acc1, sbase + OFF_B + 3 * B_BLK, warp, lane);
          fence_async_smem();
          __syncwarp();
          mbar_arrive_if(lead, bars + (BAR_QFULL + 1) * 8, 2);
        }
      }
      TRACE(8 + u);
    }
    cluster_sync();
  } else {
    asm volatile("setmaxnreg.inc.sync.aligned.u32 144;");
    const int si = wg - 1;
    ARing r{0, 0};
    uint32_t qm = 0;
    const uint32_t st_off = (16 * warp + (lane & 15)) * 64 + (((lane >> 4) ^ ((lane & 7) >> 1)) << 4);
#pragma unroll 1
    for (int u = 0;; u++) {
      const int ty = sc.type(u);
      if (ty == U_END) break;
      const bool mc_next = sc.mc(u + 1);
      TRACE(16 + si * 16 + u);
      if (ty == U_AT) {
        const uint32_t qb = sc.qbuf(u);
        if (sc.qloaded(u)) qm ^= 1u << qb;
        PROF(12 + 8 * si, mbar_wait(bars + (BAR_QFULL + qb) * 8, ((qm >> qb) & 1) ^ 1));
        const uint64_t dq = make_desc_n(sbase + OFF_B + 2 * qb * B_BLK);
        const uint32_t paddr = sbase + OFF_B + (4 + si) * B_BLK + st_off;
        float l[40];
#pragma unroll
        for (int i = 0; i < 40; i++) l[i] = 0.f;
        r.adv(si);
        mbar_wait(bars + (BAR_XEMPTY + 2 + si) * 8, 1);
        bool kok = false;
#pragma unroll 1
        for (int t = 0; t < 8; t++) {
          float acc[80];
          if (!kok) PROF(13 + 8 * si, mbar_wait(bars + (BAR_FS + si + 2 * (t & 1)) * 8, (t >> 1) & 1));
          STAMP((2 * t + si) * 6);
          const uint64_t dk = make_desc(sbase + r.slot * A_SLOT);
          wgmma_fence();
          wgmma_160_init<0, 1>(acc, dk, dq);
#pragma unroll
          for (int kk = 1; kk < 8; kk++)
            wgmma_160<0, 1>(acc, dk + (kk >> 2) * 512 + (kk & 3) * 2, dq + (kk >> 2) * (B_BLK / 16) + (kk & 3) * 64);
          wgmma_commit();
          STAMP((2 * t + si) * 6 + 1);
          PROF(14 + 8 * si, wgmma_wait<0>());
          STAMP((2 * t + si) * 6 + 2);
          release_a(bars, r.slot, t == 7 ? mc_next : false, peer, 2, lead);
          r.adv((t == 0 && si == 0) ? 3 : (t == 7 ? 5 - 2 * si : 4));
          auto expo = [&](int j) {
#pragma unroll
            for (int i = 0; i < 8; i++) acc[8 * j + i] = ex2(acc[8 * j + i]);
          };
          auto consume = [&](int j) {
            l[4 * j] += acc[8 * j] + acc[8 * j + 2];
            l[4 * j + 1] += acc[8 * j + 1] + acc[8 * j + 3];
            l[4 * j + 2] += acc[8 * j + 4] + acc[8 * j + 6];
            l[4 * j + 3] += acc[8 * j + 5] + acc[8 * j + 7];
            stsm_x4(n_addr(paddr, j), pack_bf16(acc[8 * j], acc[8 * j + 1]), pack_bf16(acc[8 * j + 2], acc[8 * j + 3]),
                    pack_bf16(acc[8 * j + 4], acc[8 * j + 5]), pack_bf16(acc[8 * j + 6], acc[8 * j + 7]));
          };
#pragma unroll
          for (int j = 0; j < SM_A - 2; j++) expo(j);
          sched_fence(zero);
          const bool pok = mbar_test(bars + (BAR_PEMPTY + si) * 8, (t & 1) ^ 1);
          expo(SM_A - 2);
          expo(SM_A - 1);
          STAMP((2 * t + si) * 6 + 3);
          if (!pok) PROF(15 + 8 * si, mbar_wait(bars + (BAR_PEMPTY + si) * 8, (t & 1) ^ 1));
          STAMP((2 * t + si) * 6 + 4);
#pragma unroll
          for (int j = SM_A; j < SM_B; j++) expo(j);
#pragma unroll
          for (int j = 0; j < SM_A; j++) consume(j);
          sched_fence(zero);
#pragma unroll
          for (int j = SM_B; j < 10; j++) expo(j);
#pragma unroll
          for (int j = SM_A; j < SM_B; j++) consume(j);
          sched_fence(zero);
#pragma unroll
          for (int j = SM_B; j < 10; j++) consume(j);
          kok = t < 7 && mbar_test(bars + (BAR_FS + si + 2 * ((t + 1) & 1)) * 8, ((t + 1) >> 1) & 1);
          fence_async_smem();
          __syncwarp();
          mbar_arrive_if(lead, bars + (BAR_PFULL + si) * 8, 1);
          STAMP((2 * t + si) * 6 + 5);
        }
        {
          const bool h4 = lane & 16, h3 = lane & 8, h2 = lane & 4;
#pragma unroll
          for (int i = 0; i < 20; i++) {
            const float send = h4 ? l[i] : l[i + 20], keep = h4 ? l[i + 20] : l[i];
            l[i] = keep + __shfl_xor_sync(0xffffffffu, send, 16);
          }
#pragma unroll
          for (int i = 0; i < 10; i++) {
            const float send = h3 ? l[i] : l[i + 10], keep = h3 ? l[i + 10] : l[i];
            l[i] = keep + __shfl_xor_sync(0xffffffffu, send, 8);
          }
#pragma unroll
          for (int i = 0; i < 5; i++) {
            const float send = h2 ? l[i] : l[i + 5], keep = h2 ? l[i + 5] : l[i];
            l[i] = keep + __shfl_xor_sync(0xffffffffu, send, 4);
          }
          float* lsum = reinterpret_cast<float*>(smem + OFF_LSUM) + (si * 4 + warp) * SQ;
          const int i0 = (h4 ? 20 : 0) + (h3 ? 10 : 0) + (h2 ? 5 : 0);
#pragma unroll
          for (int i = 0; i < 5; i++) {
            const int c = i0 + i;
            lsum[8 * (c >> 1) + 2 * (lane & 3) + (c & 1)] = l[i];
          }
          __syncwarp();
          mbar_arrive_if(lead, bars + BAR_LREADY * 8, 1);
        }
      } else {
        float acc[80];
        const int n = ty == U_OP ? 64 : 16;
        const int rot = sc.rot(u);
        const bool hq = ty == U_HQ;
        const uint32_t xcnt = hq ? 2 - si : 1, astep = hq ? 1 : 2;
        r.adv(astep - 1);
        uint32_t x = rot;
        auto mainloop = [&](auto tb) {
          constexpr int TB = decltype(tb)::value;
          constexpr int KB = TB ? 64 : 2;
          mbar_wait(bars + (BAR_XFULL + x) * 8, 0);
          mbar_wait(bars + (hq ? BAR_FS : BAR_FG) * 8, 0);
          {
            const uint32_t baddr = sbase + OFF_B + (2 + x) * B_BLK;
            const uint64_t da = make_desc(sbase + r.slot * A_SLOT + si * 8192), db = TB ? make_desc_n(baddr) : make_desc(baddr);
            wgmma_fence();
            wgmma_160_init<1, TB>(acc, da, db);
#pragma unroll
            for (int kk = 1; kk < 4; kk++) wgmma_160<1, TB>(acc, da + kk * 128, db + kk * KB);
            wgmma_commit();
          }
#pragma unroll 1
          for (int s = 1; s < n; s++) {
            const uint32_t pslot = r.slot, px = x;
            r.adv(astep);
            x = (s + rot) & 3;
            const uint32_t afull = bars + (((hq && !(s & 4)) ? BAR_FS : BAR_FG) + (s & 3)) * 8, apar = (s >> (hq ? 3 : 2)) & 1;
            const bool okb = mbar_test(bars + (BAR_XFULL + x) * 8, (s >> 2) & 1), oka = mbar_test(afull, apar);
            const uint32_t baddr = sbase + OFF_B + (2 + x) * B_BLK;
            const uint64_t da = make_desc(sbase + r.slot * A_SLOT + si * 8192), db = TB ? make_desc_n(baddr) : make_desc(baddr);
            PROF(18 + 8 * si, wgmma_wait<0>());
            mbar_arrive_if(lead, bars + (BAR_XEMPTY + px) * 8, xcnt);
            release_a(bars, pslot, astep * s - 1 + NA < astep * n ? true : mc_next, peer, 1, lead);
            if (!okb) PROF(16 + 8 * si, mbar_wait(bars + (BAR_XFULL + x) * 8, (s >> 2) & 1));
            if (!oka) PROF(17 + 8 * si, mbar_wait(afull, apar));
            wgmma_fence();
#pragma unroll
            for (int kk = 0; kk < 4; kk++) wgmma_160<1, TB>(acc, da + kk * 128, db + kk * KB);
            wgmma_commit();
          }
          wgmma_wait<0>();
          mbar_arrive_if(lead, bars + (BAR_XEMPTY + x) * 8, xcnt);
          release_a(bars, r.slot, mc_next, peer, 1, lead);
          r.adv(1);
          PROF(19 + 8 * si, mbar_wait(bars + BAR_QEMPTY * 8, (qm & 1) ^ 1));
        };
        if (ty != U_OP) {
          mainloop(Int<0>{});
          store_block_n(acc, Q_SCALE, sbase + OFF_B + si * B_BLK + st_off);
        } else {
          mainloop(Int<1>{});
          store_block_t(acc, sbase + OFF_B + si * B_BLK, warp, lane);
        }
        fence_async_smem();
        __syncwarp();
        mbar_arrive_if(lead, bars + BAR_QFULL * 8, 1);
        qm ^= hq ? 1 : 3;
      }
      TRACE(24 + si * 16 + u);
    }
    cluster_sync();
  }
}

typedef CUresult (*EncodeFn)(CUtensorMap*, CUtensorMapDataType, cuuint32_t, void*, const cuuint64_t*, const cuuint64_t*,
                             const cuuint32_t*, const cuuint32_t*, CUtensorMapInterleave, CUtensorMapSwizzle,
                             CUtensorMapL2promotion, CUtensorMapFloatOOBfill);

void make_map_2d(EncodeFn enc, CUtensorMap* m, const void* p, uint64_t cols, uint64_t rows, uint32_t box_rows) {
  cuuint64_t dims[2] = {cols, rows}, strides[1] = {cols * 2};
  cuuint32_t box[2] = {64, box_rows}, es[2] = {1, 1};
  enc(m, CU_TENSOR_MAP_DATA_TYPE_BFLOAT16, 2, const_cast<void*>(p), dims, strides, box, es, CU_TENSOR_MAP_INTERLEAVE_NONE,
      CU_TENSOR_MAP_SWIZZLE_128B, W_PROMO, CU_TENSOR_MAP_FLOAT_OOB_FILL_NONE);
}
void make_map_kv(EncodeFn enc, CUtensorMap* m, const void* p) {
  cuuint64_t dims[3] = {64, (cuuint64_t)NB * NH * SK, 2}, strides[2] = {DH * 2, 128};
  cuuint32_t box[3] = {64, 64, 2}, es[3] = {1, 1, 1};
  enc(m, CU_TENSOR_MAP_DATA_TYPE_BFLOAT16, 3, const_cast<void*>(p), dims, strides, box, es, CU_TENSOR_MAP_INTERLEAVE_NONE,
      CU_TENSOR_MAP_SWIZZLE_128B, KV_PROMO, CU_TENSOR_MAP_FLOAT_OOB_FILL_NONE);
}

void make_map_lines(EncodeFn enc, CUtensorMap* m, const void* p) {
  cuuint64_t dims[2] = {64, (cuuint64_t)NB * NH * SK * 2}, strides[1] = {128};
  cuuint32_t box[2] = {8, 128}, es[2] = {1, 1};
  enc(m, CU_TENSOR_MAP_DATA_TYPE_BFLOAT16, 2, const_cast<void*>(p), dims, strides, box, es, CU_TENSOR_MAP_INTERLEAVE_NONE,
      CU_TENSOR_MAP_SWIZZLE_NONE, CU_TENSOR_MAP_L2_PROMOTION_L2_128B, CU_TENSOR_MAP_FLOAT_OOB_FILL_NONE);
}

}

extern "C" void kernel_launch(void* const* d_in, const int* in_sizes, int n_in, void* d_out, int out_size) {
  (void)in_sizes; (void)n_in; (void)out_size;
  void* fn = nullptr;
  cudaDriverEntryPointQueryResult qr;
  cudaGetDriverEntryPoint("cuTensorMapEncodeTiled", &fn, cudaEnableDefault, &qr);
  EncodeFn enc = reinterpret_cast<EncodeFn>(fn);
  Maps maps;
  Ptrs ptrs;
  for (int br = 0; br < 2; br++) {
    void* const* in = d_in + 5 * br;
    make_map_2d(enc, &maps.x[br], in[0], DM, NB * SQ, SQ);
    make_map_kv(enc, &maps.k[br], in[1]);
    make_map_kv(enc, &maps.v[br], in[2]);
    make_map_lines(enc, &maps.kline[br], in[1]);
    make_map_lines(enc, &maps.vline[br], in[2]);
    make_map_2d(enc, &maps.wq[br], in[3], NH * DH, DM, 64);
    make_map_2d(enc, &maps.wo[br], in[4], DM, NH * DH, 64);
    ptrs.k[br] = static_cast<const __nv_bfloat16*>(in[1]);
    ptrs.v[br] = static_cast<const __nv_bfloat16*>(in[2]);
  }
  make_map_2d(enc, &maps.out, d_out, 2 * DM, NB * SQ, SQ);
  cudaFuncSetAttribute(mha2_kernel, cudaFuncAttributeMaxDynamicSharedMemorySize, SMEM_BYTES);
  cudaLaunchConfig_t cfg = {};
  cfg.gridDim = 132;
  cfg.blockDim = 512;
  cfg.dynamicSmemBytes = SMEM_BYTES;
  int ncl = 0;
  cudaOccupancyMaxActiveClusters(&ncl, mha2_kernel, &cfg);
  ncl = ncl > 66 ? 66 : (ncl < 64 ? 64 : ncl);
  mha2_kernel<<<2 * ncl, 512, SMEM_BYTES, cudaStreamPerThread>>>(maps, ptrs);
}
```

```cpp
#include <cuda_runtime.h>
#include <cuda_bf16.h>
#include <cuda.h>
#include <stdint.h>
#include <algorithm>

namespace {

constexpr int SQ = 160, DM = 1024, NH = 32, SK = 1024, DH = 128, NB = 8;
constexpr int A_SLOT = 16384, NA = 6;
constexpr int B_BLK = 20480;
constexpr int OFF_B = NA * A_SLOT;
constexpr int OFF_LSUM = OFF_B + 6 * B_BLK;
constexpr int OFF_LINV = OFF_LSUM + 8 * SQ * 4;
constexpr int OFF_BAR = OFF_LINV + SQ * 4;
constexpr int OFF_SINK = OFF_BAR + 640 + 1024;
constexpr int SMEM_BYTES = OFF_SINK + 2048 + 1024;
constexpr int BAR_FO = 47, BAR_FG = 41, BAR_BANK = 45, BAR_GLAST = 46, BAR_ORD = 55, BAR_FS = 0, BAR_AEMPTY = 6, BAR_XFULL = 12, BAR_XEMPTY = 16, BAR_PFULL = 20, BAR_PEMPTY = 22,
              BAR_QFULL = 24, BAR_QEMPTY = 26, BAR_LREADY = 28, BAR_OSTORE = 29, BAR_PDONE = 30,
              BAR_REMPTY = 31;
constexpr float Q_SCALE = 0.08838834764831845f * 1.4426950408889634f;
constexpr uint32_t SPIN_LIMIT = 1u << 26;

#define KV_PROMO CU_TENSOR_MAP_L2_PROMOTION_L2_128B
#define X_PROMO CU_TENSOR_MAP_L2_PROMOTION_L2_128B
#define W_PROMO CU_TENSOR_MAP_L2_PROMOTION_L2_128B

#define JSTAR 3
#define E_SHIFT 0
#define OP_GATE 24
#define USE_E 1
#define QK_FIRST 1
#define SLEEP_MASK 6
#define MW_A(b, p) ((SLEEP_MASK & 1) ? mbar_wait_sleep(b, p) : mbar_wait(b, p))
#define MW_B(b, p) ((SLEEP_MASK & 2) ? mbar_wait_sleep(b, p) : mbar_wait(b, p))
#define MW_C(b, p) ((SLEEP_MASK & 4) ? mbar_wait_sleep(b, p) : mbar_wait(b, p))
#define EP_PRE 4
#define DEFER_O 1
#define G2_LATE_HQ 1
#define WQ_EF 1
#define WO_EF 0
#define OP_S_FIRST 2
#define COLD_STAGGER 250
#define END_SYNC 0
#define DYN 4
#define X_LATE 1
#define O_LAST 0
#define ST_PACE 0
#define ST_SLEEP 0
#define BANK_N 12
#define BANK_FIRST 3
#define BANK_DELAY 1500
#define BANK_PACE 330
#define PROBE_REP 2
#define W_EF 1

#define SM_A 4
#define SM_B 7

#define WAIT_HINT 0

#define SIDE_AWARE 1
#define LOCAL_SCRATCH 1

struct Maps {
  CUtensorMap x[2], wq[2], wo[2], k[2], v[2], kline[2], vline[2], out;
};
struct Ptrs {
  const __nv_bfloat16* k[2];
  const __nv_bfloat16* v[2];
};

constexpr int PAGE = 2 << 20, SLOTS_PER_PAGE = 25, SLOT_SPAN = 81920, PROBE_OFF = SLOTS_PER_PAGE * SLOT_SPAN;
constexpr uint32_t PART_MASK = (1u << 13) | (1u << 16) | (1u << 17) | (1u << 19);
__device__ uint4 g_scratch[22 * (PAGE / 16)];
__device__ uint32_t g_claim, g_claim_done;
__device__ __align__(16) uint32_t g_qflag[2 * NB * NH];
__device__ uint4 g_oflag[2 * NB * NH];

__device__ __forceinline__ uint32_t smem_u32(const void* p) { return (uint32_t)__cvta_generic_to_shared(p); }
__device__ __forceinline__ bool elect_one() {
  uint32_t p;
  asm volatile("{\n.reg .pred p;\nelect.sync _|p, 0xffffffff;\nselp.b32 %0, 1, 0, p;\n}\n" : "=r"(p));
  return p;
}
__device__ __forceinline__ void mbar_init(uint32_t bar, uint32_t cnt) {
  asm volatile("mbarrier.init.shared::cta.b64 [%0], %1;" ::"r"(bar), "r"(cnt));
}
__device__ __forceinline__ void mbar_arrive_expect_tx(uint32_t bar, uint32_t bytes) {
  asm volatile("mbarrier.arrive.expect_tx.shared::cta.b64 _, [%0], %1;" ::"r"(bar), "r"(bytes) : "memory");
}
__device__ __forceinline__ void mbar_expect_tx(uint32_t bar, uint32_t bytes) {
  asm volatile("mbarrier.expect_tx.relaxed.cta.shared::cta.b64 [%0], %1;" ::"r"(bar), "r"(bytes) : "memory");
}
__device__ __forceinline__ void mbar_arrive(uint32_t bar, uint32_t cnt) {
  asm volatile("mbarrier.arrive.shared::cta.b64 _, [%0], %1;" ::"r"(bar), "r"(cnt) : "memory");
}
__device__ __forceinline__ void mbar_arrive_n(uint32_t n, uint32_t bar) {
  asm volatile("{\n.reg .pred p;\n.reg .b32 l;\nmov.u32 l, %%laneid;\nsetp.lt.u32 p, l, %1;\n"
               "@p mbarrier.arrive.shared::cta.b64 _, [%0];\n}\n" ::"r"(bar), "r"(n) : "memory");
}
__device__ __forceinline__ void mbar_arrive_remote_n(uint32_t n, uint32_t bar, uint32_t cta) {
  asm volatile(
      "{\n.reg .pred p;\n.reg .b32 ra, l;\nmov.u32 l, %%laneid;\nsetp.lt.u32 p, l, %2;\nmapa.shared::cluster.u32 ra, %0, %1;\n"
      "@p mbarrier.arrive.shared::cluster.b64 _, [ra];\n}\n" ::"r"(bar), "r"(cta), "r"(n) : "memory");
}
__device__ __forceinline__ void mbar_wait(uint32_t bar, uint32_t parity) {
  asm volatile(
      "{\n.reg .pred p;\n.reg .b32 n;\nmov.b32 n, 0;\n"
      "WAIT_%=:\n"
      "mbarrier.try_wait.parity.shared::cta.b64 p, [%0], %1;\n"
      "@p bra DONE_%=;\n"
      "add.u32 n, n, 1;\n"
      "setp.lt.u32 p, n, %2;\n"
      "@p bra WAIT_%=;\n"
      "trap;\n"
      "DONE_%=:\n}\n" ::"r"(bar), "r"(parity), "n"(SPIN_LIMIT), "n"(WAIT_HINT) : "memory");
}
__device__ __forceinline__ void mbar_wait_sleep(uint32_t bar, uint32_t parity) {
  asm volatile(
      "{\n.reg .pred p;\n.reg .b32 n;\nmov.b32 n, 0;\n"
      "WAIT_%=:\n"
      "mbarrier.try_wait.parity.shared::cta.b64 p, [%0], %1, %3;\n"
      "@p bra DONE_%=;\n"
      "add.u32 n, n, 1;\n"
      "setp.lt.u32 p, n, %2;\n"
      "@p bra WAIT_%=;\n"
      "trap;\n"
      "DONE_%=:\n}\n" ::"r"(bar), "r"(parity), "n"(SPIN_LIMIT >> 4), "n"(4000) : "memory");
}
__device__ __forceinline__ bool mbar_test(uint32_t bar, uint32_t parity) {
  uint32_t ok;
  asm volatile("{\n.reg .pred p;\nmbarrier.test_wait.parity.shared::cta.b64 p, [%1], %2;\nselp.b32 %0, 1, 0, p;\n}\n"
               : "=r"(ok) : "r"(bar), "r"(parity) : "memory");
  return ok;
}
__device__ __forceinline__ void tma_prefetch_2d(const CUtensorMap* m, int c0, int c1) {
  asm volatile("cp.async.bulk.prefetch.tensor.2d.L2.global [%0, {%1, %2}];" ::"l"(m), "r"(c0), "r"(c1) : "memory");
}
__device__ __forceinline__ void tma_2d(uint32_t dst, const CUtensorMap* m, int c0, int c1, uint32_t bar) {
  asm volatile(
      "cp.async.bulk.tensor.2d.shared::cluster.global.mbarrier::complete_tx::bytes [%0], [%1, {%3, %4}], [%2];" ::"r"(dst),
      "l"(m), "r"(bar), "r"(c0), "r"(c1) : "memory");
}
__device__ __forceinline__ void tma_2d_mc(uint32_t dst, const CUtensorMap* m, int c0, int c1, uint32_t bar, uint64_t pol) {
  asm volatile(
      "cp.async.bulk.tensor.2d.shared::cluster.global.mbarrier::complete_tx::bytes.multicast::cluster.L2::cache_hint"
      " [%0], [%1, {%3, %4}], [%2], %5, %6;" ::"r"(dst), "l"(m), "r"(bar), "r"(c0), "r"(c1), "h"((uint16_t)3), "l"(pol) : "memory");
}
__device__ __forceinline__ void tma_3d_hint(uint32_t dst, const CUtensorMap* m, int c1, uint32_t bar, uint64_t pol) {
  asm volatile(
      "cp.async.bulk.tensor.3d.shared::cluster.global.mbarrier::complete_tx::bytes.L2::cache_hint"
      " [%0], [%1, {%4, %3, %4}], [%2], %5;" ::"r"(dst), "l"(m), "r"(bar), "r"(c1), "r"(0), "l"(pol) : "memory");
}
__device__ __forceinline__ void tma_store_2d(const CUtensorMap* m, int c0, int c1, uint32_t src) {
  asm volatile("cp.async.bulk.tensor.2d.global.shared::cta.bulk_group [%0, {%2, %3}], [%1];" ::"l"(m), "r"(src), "r"(c0),
               "r"(c1) : "memory");
}
__device__ __forceinline__ void bulk_g2s(uint32_t dst, const void* src, uint32_t bytes, uint32_t bar) {
  asm volatile("cp.async.bulk.shared::cluster.global.mbarrier::complete_tx::bytes [%0], [%1], %2, [%3];" ::"r"(dst),
               "l"(src), "r"(bytes), "r"(bar) : "memory");
}
__device__ __forceinline__ void bulk_s2g(void* dst, uint32_t src, uint32_t bytes) {
  asm volatile("cp.async.bulk.global.shared::cta.bulk_group [%0], [%1], %2;" ::"l"(dst), "r"(src), "r"(bytes) : "memory");
}
__device__ __forceinline__ void bulk_prefetch(const void* src, uint32_t bytes, uint64_t pol) {
  asm volatile("cp.async.bulk.prefetch.L2.global.L2::cache_hint [%0], %1, %2;" ::"l"(src), "r"(bytes), "l"(pol) : "memory");
}
__device__ __forceinline__ void bulk_prefetch(const void* src, uint32_t bytes) {
  asm volatile("cp.async.bulk.prefetch.L2.global [%0], %1;" ::"l"(src), "r"(bytes) : "memory");
}
__device__ __forceinline__ void bulk_commit() { asm volatile("cp.async.bulk.commit_group;" ::: "memory"); }
template <int N> __device__ __forceinline__ void bulk_wait_read() { asm volatile("cp.async.bulk.wait_group.read %0;" ::"n"(N) : "memory"); }
template <int N> __device__ __forceinline__ void bulk_wait() { asm volatile("cp.async.bulk.wait_group %0;" ::"n"(N) : "memory"); }
__device__ __forceinline__ void fence_async_smem() { asm volatile("fence.proxy.async.shared::cta;" ::: "memory"); }
__device__ __forceinline__ void fence_async_global() { asm volatile("fence.proxy.async.global;" ::: "memory"); }
__device__ __forceinline__ void wgmma_fence() { asm volatile("wgmma.fence.sync.aligned;" ::: "memory"); }
__device__ __forceinline__ void wgmma_commit() { asm volatile("wgmma.commit_group.sync.aligned;" ::: "memory"); }
template <int N> __device__ __forceinline__ void wgmma_wait() { asm volatile("wgmma.wait_group.sync.aligned %0;" ::"n"(N) : "memory"); }
__device__ __forceinline__ void cluster_sync() {
  asm volatile("barrier.cluster.arrive.relaxed;\nbarrier.cluster.wait;" ::: "memory");
}
__device__ __forceinline__ uint64_t make_desc(uint32_t addr) {
  return (uint64_t)((addr & 0x3FFFF) >> 4) | ((uint64_t)1 << 16) | ((uint64_t)64 << 32) | ((uint64_t)1 << 62);
}
__device__ __forceinline__ uint64_t make_desc_n(uint32_t addr) {
  return (uint64_t)((addr & 0x3FFFF) >> 4) | ((uint64_t)256 << 16) | ((uint64_t)32 << 32) | ((uint64_t)2 << 62);
}
__device__ __forceinline__ float ex2(float x) {
  float y;
  asm volatile("ex2.approx.ftz.f32 %0, %1;" : "=f"(y) : "f"(x));
  return y;
}
__device__ __forceinline__ void sched_fence(uint32_t zero) {
  asm volatile("{\n.reg .pred p;\nsetp.eq.b32 p, %0, 0;\nFENCE_%=:\n@p bra.uni FDONE_%=;\nnanosleep.u32 1;\nbra.uni FENCE_%=;\nFDONE_%=:\n}\n" ::"r"(zero) : "memory");
}
__device__ __forceinline__ uint32_t pack_bf16(float lo, float hi) {
  uint32_t r;
  asm("cvt.rn.bf16x2.f32 %0, %1, %2;" : "=r"(r) : "f"(hi), "f"(lo));
  return r;
}
__device__ __forceinline__ void stsm_x4_t(uint32_t addr, uint32_t r0, uint32_t r1, uint32_t r2, uint32_t r3) {
  asm volatile("stmatrix.sync.aligned.m8n8.x4.trans.shared.b16 [%0], {%1, %2, %3, %4};" ::"r"(addr), "r"(r0), "r"(r1),
               "r"(r2), "r"(r3) : "memory");
}
__device__ __forceinline__ void stsm_x4(uint32_t addr, uint32_t r0, uint32_t r1, uint32_t r2, uint32_t r3) {
  asm volatile("stmatrix.sync.aligned.m8n8.x4.shared.b16 [%0], {%1, %2, %3, %4};" ::"r"(addr), "r"(r0), "r"(r1), "r"(r2),
               "r"(r3) : "memory");
}
__device__ __forceinline__ uint32_t wait_flag(const uint32_t* f) {
  uint32_t v, n = 0;
  while (true) {
    asm volatile("ld.acquire.gpu.global.u32 %0, [%1];" : "=r"(v) : "l"(f) : "memory");
    if (v) break;
    if (++n > (SPIN_LIMIT >> 2)) __trap();
    __nanosleep(32);
  }
  fence_async_global();
  return __shfl_sync(0xffffffffu, v, 0);
}

__device__ __forceinline__ uint8_t* scratch_base() {
  return reinterpret_cast<uint8_t*>((reinterpret_cast<uintptr_t>(g_scratch) + PAGE - 1) & ~(uintptr_t)(PAGE - 1));
}
__device__ __forceinline__ uint32_t slot_off(uint32_t slot) {
  return (slot / SLOTS_PER_PAGE) * PAGE + (slot % SLOTS_PER_PAGE) * SLOT_SPAN;
}
__device__ __forceinline__ uint32_t piece_off(uint32_t off, uint32_t sel) {
  return off + (((__popc(off & PART_MASK) ^ sel) & 1) << 12);
}
__device__ __forceinline__ uint32_t local_selector(uint8_t* page, uint32_t pair, uint32_t id, int lane) {
  const uint32_t off = PROBE_OFF + pair * 8192;
  uint8_t *p0 = page + piece_off(off, 0) + id * 32, *p1 = page + piece_off(off, 1) + id * 32;
  if (lane < 4) asm volatile("st.global.v4.u32 [%0], {0, 0, 0, 0};" ::"l"((lane & 2 ? p1 : p0) + (lane & 1) * 16) : "memory");
  __syncwarp();
  uint32_t t1 = 0, t2 = 0;
  if (lane == 0)
    asm volatile(
        "{\n.reg .b32 a, b;\n"
        "atom.relaxed.gpu.global.exch.b32 a, [%2], 1;\natom.relaxed.gpu.global.exch.b32 b, [%3], 1;\n"
        "{\n.reg .pred p;\nsetp.eq.u32 p, a, 0xffffffff;\n@p trap;\n}\n"
        "mov.u32 %0, %%clock;\n"
        "{\n.reg .pred p;\nsetp.eq.u32 p, b, 0xffffffff;\n@p trap;\n}\n"
        "mov.u32 %1, %%clock;\n}\n"
        : "=r"(t1), "=r"(t2) : "l"(p0), "l"(p1) : "memory");
  return __shfl_sync(0xffffffffu, t2 - t1 > 100 ? 0u : 1u, 0);
}

template <int TA, int TB>
__device__ __forceinline__ void wgmma_160(float (&d)[80], uint64_t descA, uint64_t descB) {
  asm volatile(
      "wgmma.mma_async.sync.aligned.m64n160k16.f32.bf16.bf16 {"
      "%0, %1, %2, %3, %4, %5, %6, %7, %8, %9, %10, %11, %12, %13, %14, %15, "
      "%16, %17, %18, %19, %20, %21, %22, %23, %24, %25, %26, %27, %28, %29, %30, %31, "
      "%32, %33, %34, %35, %36, %37, %38, %39, %40, %41, %42, %43, %44, %45, %46, %47, "
      "%48, %49, %50, %51, %52, %53, %54, %55, %56, %57, %58, %59, %60, %61, %62, %63, "
      "%64, %65, %66, %67, %68, %69, %70, %71, %72, %73, %74, %75, %76, %77, %78, %79}, "
      "%80, %81, 1, 1, 1, %82, %83;\n"
      : "+f"(d[0]), "+f"(d[1]), "+f"(d[2]), "+f"(d[3]), "+f"(d[4]), "+f"(d[5]), "+f"(d[6]), "+f"(d[7]),
        "+f"(d[8]), "+f"(d[9]), "+f"(d[10]), "+f"(d[11]), "+f"(d[12]), "+f"(d[13]), "+f"(d[14]), "+f"(d[15]),
        "+f"(d[16]), "+f"(d[17]), "+f"(d[18]), "+f"(d[19]), "+f"(d[20]), "+f"(d[21]), "+f"(d[22]), "+f"(d[23]),
        "+f"(d[24]), "+f"(d[25]), "+f"(d[26]), "+f"(d[27]), "+f"(d[28]), "+f"(d[29]), "+f"(d[30]), "+f"(d[31]),
        "+f"(d[32]), "+f"(d[33]), "+f"(d[34]), "+f"(d[35]), "+f"(d[36]), "+f"(d[37]), "+f"(d[38]), "+f"(d[39]),
        "+f"(d[40]), "+f"(d[41]), "+f"(d[42]), "+f"(d[43]), "+f"(d[44]), "+f"(d[45]), "+f"(d[46]), "+f"(d[47]),
        "+f"(d[48]), "+f"(d[49]), "+f"(d[50]), "+f"(d[51]), "+f"(d[52]), "+f"(d[53]), "+f"(d[54]), "+f"(d[55]),
        "+f"(d[56]), "+f"(d[57]), "+f"(d[58]), "+f"(d[59]), "+f"(d[60]), "+f"(d[61]), "+f"(d[62]), "+f"(d[63]),
        "+f"(d[64]), "+f"(d[65]), "+f"(d[66]), "+f"(d[67]), "+f"(d[68]), "+f"(d[69]), "+f"(d[70]), "+f"(d[71]),
        "+f"(d[72]), "+f"(d[73]), "+f"(d[74]), "+f"(d[75]), "+f"(d[76]), "+f"(d[77]), "+f"(d[78]), "+f"(d[79])
      : "l"(descA), "l"(descB), "n"(TA), "n"(TB));
}
template <int TA, int TB>
__device__ __forceinline__ void wgmma_160_init(float (&d)[80], uint64_t descA, uint64_t descB) {
  asm volatile(
      "wgmma.mma_async.sync.aligned.m64n160k16.f32.bf16.bf16 {"
      "%0, %1, %2, %3, %4, %5, %6, %7, %8, %9, %10, %11, %12, %13, %14, %15, "
      "%16, %17, %18, %19, %20, %21, %22, %23, %24, %25, %26, %27, %28, %29, %30, %31, "
      "%32, %33, %34, %35, %36, %37, %38, %39, %40, %41, %42, %43, %44, %45, %46, %47, "
      "%48, %49, %50, %51, %52, %53, %54, %55, %56, %57, %58, %59, %60, %61, %62, %63, "
      "%64, %65, %66, %67, %68, %69, %70, %71, %72, %73, %74, %75, %76, %77, %78, %79}, "
      "%80, %81, 0, 1, 1, %82, %83;\n"
      : "=f"(d[0]), "=f"(d[1]), "=f"(d[2]), "=f"(d[3]), "=f"(d[4]), "=f"(d[5]), "=f"(d[6]), "=f"(d[7]),
        "=f"(d[8]), "=f"(d[9]), "=f"(d[10]), "=f"(d[11]), "=f"(d[12]), "=f"(d[13]), "=f"(d[14]), "=f"(d[15]),
        "=f"(d[16]), "=f"(d[17]), "=f"(d[18]), "=f"(d[19]), "=f"(d[20]), "=f"(d[21]), "=f"(d[22]), "=f"(d[23]),
        "=f"(d[24]), "=f"(d[25]), "=f"(d[26]), "=f"(d[27]), "=f"(d[28]), "=f"(d[29]), "=f"(d[30]), "=f"(d[31]),
        "=f"(d[32]), "=f"(d[33]), "=f"(d[34]), "=f"(d[35]), "=f"(d[36]), "=f"(d[37]), "=f"(d[38]), "=f"(d[39]),
        "=f"(d[40]), "=f"(d[41]), "=f"(d[42]), "=f"(d[43]), "=f"(d[44]), "=f"(d[45]), "=f"(d[46]), "=f"(d[47]),
        "=f"(d[48]), "=f"(d[49]), "=f"(d[50]), "=f"(d[51]), "=f"(d[52]), "=f"(d[53]), "=f"(d[54]), "=f"(d[55]),
        "=f"(d[56]), "=f"(d[57]), "=f"(d[58]), "=f"(d[59]), "=f"(d[60]), "=f"(d[61]), "=f"(d[62]), "=f"(d[63]),
        "=f"(d[64]), "=f"(d[65]), "=f"(d[66]), "=f"(d[67]), "=f"(d[68]), "=f"(d[69]), "=f"(d[70]), "=f"(d[71]),
        "=f"(d[72]), "=f"(d[73]), "=f"(d[74]), "=f"(d[75]), "=f"(d[76]), "=f"(d[77]), "=f"(d[78]), "=f"(d[79])
      : "l"(descA), "l"(descB), "n"(TA), "n"(TB));
}

enum { U_QP = 0, U_AT = 1, U_OP = 2, U_HQ = 3, U_END = 4 };
constexpr int MAX_UNITS = 9, MAX_ROLES = 33;
struct Plan {
  uint32_t unit[MAX_ROLES][MAX_UNITS];
  uint8_t op_head[NH];
};
struct Unit {
  uint32_t d;
  __device__ __forceinline__ int type() const { return d & 7; }
  __device__ __forceinline__ int arg() const { return (d >> 3) & 31; }
  __device__ __forceinline__ int bp() const { return (d >> 8) & 3; }
  __device__ __forceinline__ int qbuf() const { return (d >> 10) & 1; }
  __device__ __forceinline__ bool qloaded() const { return (d >> 11) & 1; }
  __device__ __forceinline__ bool keep0() const { return (d >> 12) & 1; }
  __device__ __forceinline__ bool keep1() const { return (d >> 17) & 1; }
  __device__ __forceinline__ bool bank() const { return (d >> 13) & 1; }
  __device__ __forceinline__ int rot() const { return (d >> 13) & 2; }
  __device__ __forceinline__ bool prev_at() const { return (d >> 15) & 1; }
  __device__ __forceinline__ bool next_at() const { return (d >> 18) & 1; }
  __device__ __forceinline__ bool mc_next() const { return (d >> 16) & 1; }
};

__device__ __forceinline__ uint32_t x_block(int s, int rot) {
  return (X_LATE && rot && s < 16) ? (0x44e4e4eeu >> (2 * s)) & 3 : (s + rot) & 3;
}
__device__ __forceinline__ uint32_t x_parity(int s, int rot) {
  return (X_LATE && rot && s < 16) ? (0xcf0cu >> s) & 1 : (s >> 2) & 1;
}

template <int V> struct Int { static constexpr int value = V; };

struct ARing {
  uint32_t slot, phase;
  __device__ __forceinline__ void adv(uint32_t n) {
    slot += n;
    if (slot >= NA) { slot -= NA; phase ^= 1; }
  }
};

__device__ __forceinline__ void release_a(uint32_t bars, uint32_t slot, bool next_mc, uint32_t peer, uint32_t cnt) {
  const uint32_t bar = bars + (BAR_AEMPTY + slot) * 8;
  mbar_arrive_n(cnt, bar);
  mbar_arrive_remote_n(next_mc ? cnt : 0u, bar + (BAR_REMPTY - BAR_AEMPTY) * 8, peer);
}

constexpr int OFF_ORD = 480;
__device__ __forceinline__ uint32_t read_order(uint32_t bars, int k) {
  uint32_t v;
  asm volatile(
      "{\n.reg .pred p;\n.reg .b32 n;\nmov.b32 n, 0;\n"
      "WAIT_%=:\n"
      "mbarrier.try_wait.parity.acquire.cluster.shared::cta.b64 p, [%1], 0;\n"
      "@p bra DONE_%=;\n"
      "add.u32 n, n, 1;\n"
      "setp.lt.u32 p, n, %3;\n"
      "@p bra WAIT_%=;\n"
      "trap;\n"
      "DONE_%=:\n"
      "ld.volatile.shared.u32 %0, [%2];\n}\n"
      : "=r"(v) : "r"(bars + (BAR_ORD + k) * 8), "r"(bars + OFF_ORD + k * 4), "n"(SPIN_LIMIT) : "memory");
  return __shfl_sync(0xffffffffu, v, 0);
}

__device__ __forceinline__ void store_block_t(const float (&acc)[80], uint32_t blk, int warp, int lane) {
  const uint32_t addr = blk + ((lane & 7) + ((lane >> 4) << 3)) * 128 + (((2 * warp + ((lane >> 3) & 1)) ^ (lane & 7)) << 4);
#pragma unroll
  for (int j = 0; j < 10; j++) {
    stsm_x4_t(addr + j * 2048, pack_bf16(acc[8 * j], acc[8 * j + 1]), pack_bf16(acc[8 * j + 2], acc[8 * j + 3]),
              pack_bf16(acc[8 * j + 4], acc[8 * j + 5]), pack_bf16(acc[8 * j + 6], acc[8 * j + 7]));
  }
}
__device__ __forceinline__ uint32_t n_addr(uint32_t addr0, int j) { return (addr0 ^ ((j & 1) << 5)) + (j >> 1) * 4096; }
__device__ __forceinline__ void store_block_n(const float (&acc)[80], float scale, uint32_t addr0) {
#pragma unroll
  for (int j = 0; j < 10; j++) {
    stsm_x4(n_addr(addr0, j), pack_bf16(acc[8 * j] * scale, acc[8 * j + 1] * scale),
            pack_bf16(acc[8 * j + 2] * scale, acc[8 * j + 3] * scale),
            pack_bf16(acc[8 * j + 4] * scale, acc[8 * j + 5] * scale),
            pack_bf16(acc[8 * j + 6] * scale, acc[8 * j + 7] * scale));
  }
}

#define PROF(site, stmt) stmt
#define STAMP(idx)
#define TRACE1(i)
#define TRACE(i)

__device__ __forceinline__ void slow_attention(uint8_t* qblk, const __nv_bfloat16* kp, const __nv_bfloat16* vp, int warp, int lane) {
  auto elem = [&](int d, int q) {
    return reinterpret_cast<__nv_bfloat16*>(qblk + (d >> 6) * B_BLK + (q >> 5) * 4096 + (d & 63) * 64 +
                                            ((((q >> 3) & 3) ^ ((d >> 1) & 3)) << 4) + (q & 7) * 2);
  };
#pragma unroll 1
  for (int q = warp; q < SQ; q += 4) {
    float m = -INFINITY, l = 0.f, o0 = 0.f, o1 = 0.f, o2 = 0.f, o3 = 0.f;
#pragma unroll 1
    for (int k0 = 0; k0 < SK; k0 += 32) {
      float s = 0.f;
      const uint32_t* kr = reinterpret_cast<const uint32_t*>(kp + (size_t)(k0 + lane) * DH);
#pragma unroll 1
      for (int d = 0; d < DH; d += 2) {
        const uint32_t kv = kr[d >> 1];
        s = fmaf(__bfloat162float(*elem(d, q)), __uint_as_float(kv << 16), s);
        s = fmaf(__bfloat162float(*elem(d + 1, q)), __uint_as_float(kv & 0xffff0000u), s);
      }
      float mn = s;
#pragma unroll
      for (int o = 16; o > 0; o >>= 1) mn = fmaxf(mn, __shfl_xor_sync(0xffffffffu, mn, o));
      mn = fmaxf(mn, m);
      float alpha = exp2f(m - mn), p = exp2f(s - mn);
      m = mn;
      l = l * alpha + p;
      o0 *= alpha; o1 *= alpha; o2 *= alpha; o3 *= alpha;
#pragma unroll 1
      for (int kk = 0; kk < 32; kk++) {
        float pk = __shfl_sync(0xffffffffu, p, kk);
        uint2 vv = *reinterpret_cast<const uint2*>(vp + (size_t)(k0 + kk) * DH + lane * 4);
        o0 = fmaf(pk, __uint_as_float(vv.x << 16), o0);
        o1 = fmaf(pk, __uint_as_float(vv.x & 0xffff0000u), o1);
        o2 = fmaf(pk, __uint_as_float(vv.y << 16), o2);
        o3 = fmaf(pk, __uint_as_float(vv.y & 0xffff0000u), o3);
      }
    }
#pragma unroll
    for (int o = 16; o > 0; o >>= 1) l += __shfl_xor_sync(0xffffffffu, l, o);
    float inv = 1.f / l;
    __syncwarp();
    *elem(4 * lane, q) = __float2bfloat16(o0 * inv);
    *elem(4 * lane + 1, q) = __float2bfloat16(o1 * inv);
    *elem(4 * lane + 2, q) = __float2bfloat16(o2 * inv);
    *elem(4 * lane + 3, q) = __float2bfloat16(o3 * inv);
  }
}

__global__ void __cluster_dims__(2, 1, 1) __launch_bounds__(512, 1)
mha2_kernel(const __grid_constant__ Maps maps, const __grid_constant__ Ptrs ptrs, const __grid_constant__ Plan plan) {
  extern __shared__ uint8_t smem_raw[];
  uint8_t* smem = smem_raw + ((1024 - (smem_u32(smem_raw) & 1023)) & 1023);
  const uint32_t sbase = smem_u32(smem);
  const uint32_t bars = sbase + OFF_BAR;
  const int tid = threadIdx.x, lane = tid & 31;
  const int warp = __shfl_sync(0xffffffffu, (tid >> 5) & 3, 0);
  const uint32_t zero = blockIdx.y;
  const int wg = __shfl_sync(0xffffffffu, tid >> 7, 0);
  const uint32_t rank = blockIdx.x & 1, peer = rank ^ 1;
  uint8_t* const scratch = scratch_base();
  volatile uint32_t* role_slot = reinterpret_cast<volatile uint32_t*>(smem + OFF_BAR + 504);

  uint32_t side = 0;
  if (SIDE_AWARE && (tid >> 5) == 1 && rank == 0) {
#pragma unroll 1
    for (int i = 0; i < PROBE_REP; i++) {
      side = local_selector(scratch, 5, blockIdx.x >> 1, lane);
    }
  }
  if (SIDE_AWARE && tid == 32 && rank == 0) {
    const uint32_t ncl = gridDim.x >> 1, half = ncl >> 1;
    const uint32_t old = atomicAdd(&g_claim, side ? 0x10000u : 1u);
    const uint32_t t = side ? old >> 16 : old & 0xffffu;
    uint32_t role = side * 64 + t;
    if (t >= half) {
      uint32_t v, n = 0;
      while (true) {
        asm volatile("ld.relaxed.gpu.global.u32 %0, [%1];" : "=r"(v) : "l"(&g_claim) : "memory");
        if ((v >> 16) + (v & 0xffffu) >= ncl) break;
        if (++n > (SPIN_LIMIT >> 2)) __trap();
      }
      role = (side ^ 1) * 64 + (side ? v & 0xffffu : v >> 16) + (t - half);
    }
    *role_slot = role;
    asm volatile("fence.release.sync_restrict::shared::cta.cluster;" ::: "memory");
  }
  if (tid >= 64 && tid < 64 + (int)(sizeof(Maps) / sizeof(CUtensorMap)))
    asm volatile("prefetch.tensormap [%0];" ::"l"(reinterpret_cast<const CUtensorMap*>(&maps) + (tid - 64)) : "memory");
  if (tid == 0) {
    for (int i = 0; i < NA; i++) {
      mbar_init(bars + (BAR_AEMPTY + i) * 8, 8);
      mbar_init(bars + (BAR_REMPTY + i) * 8, 8);
    }
    for (int i = 0; i < 4; i++) {
      mbar_init(bars + (BAR_XFULL + i) * 8, 1);
      mbar_init(bars + (BAR_FO + i) * 8, 1);
      mbar_init(bars + (BAR_FO + 4 + i) * 8, 1);
      mbar_init(bars + (BAR_FG + i) * 8, 1);
      mbar_init(bars + (BAR_FS + i) * 8, 1);
      mbar_init(bars + (BAR_XEMPTY + i) * 8, 12);
      mbar_init(bars + (BAR_PFULL + i) * 8, 4);
    }
    for (int i = 0; i < 2; i++) {
      mbar_init(bars + (BAR_QFULL + i) * 8, 8);
      mbar_init(bars + (BAR_QEMPTY + i) * 8, 1);
    }
    mbar_init(bars + BAR_PDONE * 8, 4);
    mbar_init(bars + BAR_BANK * 8, 1);
    mbar_init(bars + BAR_GLAST * 8, 8);
    for (int i = 0; i < DYN; i++) {
      mbar_init(bars + (BAR_ORD + i) * 8, 1);
      mbar_arrive_expect_tx(bars + (BAR_ORD + i) * 8, 4);
    }
    mbar_init(bars + BAR_LREADY * 8, 8);
    mbar_init(bars + BAR_OSTORE * 8, 4);
    asm volatile("fence.mbarrier_init.release.cluster;" ::: "memory");
  }
  __syncthreads();
  cluster_sync();
  uint32_t role;
  asm volatile("{\n.reg .b32 ra;\nmapa.shared::cluster.u32 ra, %1, 0;\nld.volatile.shared::cluster.u32 %0, [ra];\n}\n"
               : "=r"(role) : "r"(bars + 504) : "memory");
  role = SIDE_AWARE ? __shfl_sync(0xffffffffu, role, 0) : ((blockIdx.x >> 1) & 1) * 64 + (blockIdx.x >> 2);
  if (SIDE_AWARE && tid == 480 && rank == 0) {
    if (atomicAdd(&g_claim_done, 1) == (gridDim.x >> 1) - 1) {
      g_claim = 0;
      g_claim_done = 0;
    }
  }
  __syncwarp();
  const int br = role >> 6;
  const uint32_t* const units = plan.unit[role & 63];
  const int cta = (role & 63) < 32 ? (br * 32 + (role & 63)) * 2 + rank : 128 + br * 2 + rank;

  if (wg == 3) {
    asm volatile("setmaxnreg.dec.sync.aligned.u32 32;");
    if (warp == 0) {
      uint64_t pol;
      asm volatile("createpolicy.fractional.L2::evict_first.b64 %0, 1.0;" : "=l"(pol));
      uint64_t pol_wq = pol, pol_wo = pol;
      if (!WQ_EF) asm volatile("createpolicy.fractional.L2::evict_normal.b64 %0, 1.0;" : "=l"(pol_wq));
      if (!WO_EF) asm volatile("createpolicy.fractional.L2::evict_normal.b64 %0, 1.0;" : "=l"(pol_wo));
      ARing r{0, 1};
      uint32_t rm = 0x3F;
#pragma unroll 1
      for (int u = 0;; u++) {
        const Unit un{units[u]};
        const int ty = un.type();
        if (ty == U_END) break;
        const int arg = un.arg(), b = un.bp() * 2 + rank;
        if (ty == U_AT) {
          const CUtensorMap *mk = &maps.k[br], *mv = &maps.v[br];
          const int row0 = (b * NH + arg) * SK;
          const Unit nx{units[u + 1]};
          const int row_next = ((nx.bp() * 2 + rank) * NH + nx.arg()) * SK - 16 * 64;
#pragma unroll 1
          for (int j = un.prev_at() ? 0 : -2; j < 16; j++) {
            if (j < 14 || un.next_at()) {
              const uint32_t full = bars + (BAR_FS + ((j + 2) & 3)) * 8;
              PROF(0, MW_A(bars + (BAR_AEMPTY + r.slot) * 8, r.phase));
              if (elect_one()) {
                mbar_arrive_expect_tx(full, A_SLOT);
                tma_3d_hint(sbase + r.slot * A_SLOT, mk, (j < 14 ? row0 : row_next) + (j + 2) * 64, full, pol);
              }
              r.adv(1);
            }
            if (j >= 0) {
              const uint32_t full = bars + (BAR_FO + (j & 7)) * 8;
              PROF(0, MW_A(bars + (BAR_AEMPTY + r.slot) * 8, r.phase));
              if (elect_one()) {
                mbar_arrive_expect_tx(full, A_SLOT);
                tma_3d_hint(sbase + r.slot * A_SLOT, mv, row0 + j * 64, full, pol);
              }
              r.adv(1);
            }
          }
        } else {
          const CUtensorMap* mw = ty == U_OP ? &maps.wo[br] : &maps.wq[br];
          const int col = arg * (ty == U_HQ ? 128 : 256) + rank * 64;
          const int n = ty == U_OP ? 64 : 16;
          int row = 0;
          const uint64_t wpol = ty == U_OP ? pol_wo : pol_wq;
#pragma unroll 1
          for (int s = 0; s < n; s++) {
            if (ty == U_OP && (s & 1) == 0) {
              int hi = s >> 1;
              if (hi >= NH - DYN) hi = NH - DYN + (read_order(bars, hi - (NH - DYN)) & 255);
              row = plan.op_head[hi] * DH;
            }
#pragma unroll 1
            for (int i = ty == U_HQ ? 1 : 0; i < 2; i++) {
              const uint32_t full = bars + (i == 0 ? BAR_FO + (s & 7) : ((ty == U_HQ && !(s & 4) == un.keep0()) ? BAR_FS : BAR_FG) + (s & 3)) * 8;
              PROF(0, MW_A(bars + (BAR_AEMPTY + r.slot) * 8, r.phase));
              PROF(1, MW_A(bars + (BAR_REMPTY + r.slot) * 8, (rm >> r.slot) & 1));
              rm ^= 1u << r.slot;
              if (elect_one()) {
                mbar_arrive_expect_tx(full, A_SLOT);
                tma_2d_mc(sbase + r.slot * A_SLOT + rank * 8192, mw, col + (i ^ 1) * 128, row, full, wpol);
              }
              r.adv(1);
            }
            row += 64;
          }
        }
      }
    } else if (warp == 1) {
      uint32_t qm = 0, pdph = 0;
#pragma unroll 1
      for (int u = 0;; u++) {
        const Unit un{units[u]};
        const int ty = un.type();
        if (ty == U_END) break;
        const int b = un.bp() * 2 + rank, bh0 = (br * NB + b) * NH;
        if (ty == U_AT) {
          if (un.qloaded()) {
            const int slot = bh0 + un.arg(), qb = un.qbuf();
            uint32_t sel;
            PROF(2, sel = wait_flag(&g_qflag[slot]));
            const uint32_t full = bars + (BAR_QFULL + qb) * 8;
            MW_B(bars + (BAR_QEMPTY + qb) * 8, ((qm >> qb) & 1) ^ 1);
            MW_B(bars + BAR_XEMPTY * 8, 1);
            MW_B(bars + (BAR_XEMPTY + 1) * 8, 1);
            if (elect_one()) {
              g_qflag[slot] = 0;
              mbar_expect_tx(full, 2 * B_BLK);
              mbar_arrive(full, 8);
              const uint32_t off = slot_off(slot);
#pragma unroll 1
              for (int i = 0; i < 10; i++)
                bulk_g2s(sbase + OFF_B + 2 * qb * B_BLK + i * 4096, scratch + piece_off(off + i * 8192, sel), 4096, full);
            }
            qm ^= 1u << qb;
          }
        } else {
          const int n = ty == U_OP ? 64 : 16, rot = un.rot();
          const bool prev_at = un.prev_at();
          uint32_t off = 0, sel = 0, todo = (1u << DYN) - 1;
#pragma unroll 1
          for (int s = 0; s < n; s++) {
            const int x = x_block(s, rot);
            if (ty == U_OP && (s & 1) == 0) {
              int hi = s >> 1;
              if (hi >= NH - DYN) {
                const int k = hi - (NH - DYN);
                uint32_t msg;
                if (rank == 0) {
                  const int c = lane % (DYN ? DYN : 1), rk = (lane / (DYN ? DYN : 1)) & 1;
                  const uint32_t* f = reinterpret_cast<const uint32_t*>(&g_oflag[bh0 + rk * NH + plan.op_head[NH - DYN + c]]) + un.arg();
                  uint32_t v, ready, cnt = 0;
                  while (true) {
                    asm volatile("ld.acquire.gpu.global.u32 %0, [%1];" : "=r"(v) : "l"(f) : "memory");
                    const uint32_t m = __ballot_sync(0xffffffffu, v != 0);
                    ready = m & (m >> DYN) & todo;
                    if (ready) break;
                    if (++cnt > (SPIN_LIMIT >> 2)) __trap();
                  }
                  const int i = __ffs(ready) - 1;
                  todo &= ~(1u << i);
                  msg = i | (__shfl_sync(0xffffffffu, v, i) << 8) | (__shfl_sync(0xffffffffu, v, i + DYN) << 10);
                  if (lane < 2)
                    asm volatile(
                        "{\n.reg .b32 a, m;\nmapa.shared::cluster.u32 a, %0, %3;\nmapa.shared::cluster.u32 m, %1, %3;\n"
                        "st.async.weak.shared::cluster.mbarrier::complete_tx::bytes.b32 [a], %2, [m];\n}\n" ::"r"(bars + OFF_ORD + k * 4),
                        "r"(bars + (BAR_ORD + k) * 8), "r"(msg), "r"(lane) : "memory");
                } else {
                  msg = read_order(bars, k);
                }
                fence_async_global();
                hi = NH - DYN + (msg & 255);
                sel = (msg >> (8 + 2 * rank)) & 1;
              }
              const int slot = bh0 + plan.op_head[hi];
              off = slot_off(slot);
              uint32_t* f = reinterpret_cast<uint32_t*>(&g_oflag[slot]) + un.arg();
              if ((s >> 1) < NH - DYN) PROF(2, sel = wait_flag(f));
              if (s >= 52) TRACE1(56 + ((s - 52) >> 1));
              if (elect_one()) *f = 0;
            }
            if (s <= 4) {
              if (x == 0) PROF(4, MW_B(bars + (BAR_QEMPTY + 1) * 8, ((qm >> 1) & 1) ^ 1));
              if (s == 2 && prev_at) { MW_B(bars + BAR_PDONE * 8, pdph); pdph ^= 1; }
            }
            const uint32_t full = bars + (BAR_XFULL + x) * 8, dst = sbase + OFF_B + (2 + x) * B_BLK;
            PROF(3, MW_B(bars + (BAR_XEMPTY + x) * 8, x_parity(s, rot) ^ 1));
            if (elect_one()) {
              mbar_arrive_expect_tx(full, B_BLK);
              if (ty != U_OP) {
                tma_2d(dst, &maps.x[br], s * 64, b * SQ, full);
              } else {
#pragma unroll
                for (int i = 0; i < 5; i++)
                  bulk_g2s(dst + i * 4096, scratch + piece_off(off + ((s & 1) * 5 + i) * 8192, sel), 4096, full);
              }
            }
          }
          qm ^= ty == U_HQ ? 1 : 3;
        }
      }
    } else if (warp == 2) {
      uint32_t qm = 0, oph = 0;
      uint32_t known = 0, selmask = 0;
#pragma unroll 1
      for (int i = 0; LOCAL_SCRATCH; i++) {
        const Unit un{units[i >> 1]};
        if (un.type() == U_END) break;
        if (un.type() == U_OP) continue;
        const uint32_t page = ((br * NB + un.bp() * 2 + rank) * NH + (un.type() != U_QP ? un.arg() : 2 * un.arg() + (i & 1))) / SLOTS_PER_PAGE;
        if ((known >> page) & 1) continue;
        uint32_t votes = 0;
#pragma unroll 1
        for (int j = 0; j < 3; j++) votes += local_selector(scratch + page * PAGE, j, cta & 127, lane);
        known |= 1u << page;
        selmask |= (votes >> 1) << page;
      }
      auto store_slot = [&](uint32_t slot, uint32_t src, bool paced) {
        const uint32_t sel = (selmask >> (slot / SLOTS_PER_PAGE)) & 1, off = slot_off(slot);
#pragma unroll 1
        for (int i = 0; i < 10; i++) {
          bulk_s2g(scratch + piece_off(off + i * 8192, sel), src + i * 4096, 4096);
          if (paced) {
            bulk_commit();
            bulk_wait_read<0>();
            if (ST_SLEEP) __nanosleep(ST_SLEEP);
          }
        }
        bulk_commit();
        return 2 + sel;
      };
#pragma unroll 1
      for (int u = 0; lane == 0; u++) {
        const Unit un{units[u]};
        const int ty = un.type();
        if (ty == U_END) break;
        const int b = un.bp() * 2 + rank, bh0 = (br * NB + b) * NH;
        if (ty == U_AT) {
          const int slot = bh0 + un.arg(), qb = un.qbuf();
          if (un.qloaded()) qm ^= 1u << qb;
          MW_C(bars + BAR_OSTORE * 8, oph);
          oph ^= 1;
          TRACE1(52);
          const uint32_t fv = store_slot(slot, sbase + OFF_B + 2 * qb * B_BLK, (ST_PACE & 1) && (un.next_at() || un.mc_next()));
          TRACE1(53);
          bulk_wait_read<0>();
          mbar_arrive(bars + (BAR_QEMPTY + qb) * 8, 1);
          bulk_wait<0>();
          TRACE1(54);
          fence_async_global();
          asm volatile("fence.release.gpu;" ::: "memory");
          TRACE1(55);
          asm volatile("st.relaxed.gpu.global.v4.u32 [%0], {%1, %1, %1, %1};" ::"l"(&g_oflag[slot]), "r"(fv) : "memory");
        } else if (ty != U_OP) {
          const int slot = bh0 + (ty == U_QP ? 2 : 1) * un.arg();
          const int hi = (ty == U_QP && !un.keep1()) ? 1 : 0, lo = un.keep0() ? 1 : 0;
          uint32_t fv = 0;
#pragma unroll 1
          for (int h = hi; h >= lo; h--) {
            MW_C(bars + (BAR_QFULL + h) * 8, (qm >> h) & 1);
            fv |= store_slot(slot + h, sbase + OFF_B + 2 * h * B_BLK, ST_PACE & 2) << (2 * h);
            bulk_wait_read<0>();
            mbar_arrive(bars + (BAR_QEMPTY + h) * 8, 1);
          }
          if (hi >= lo) {
            bulk_wait<0>();
            fence_async_global();
            asm volatile("fence.release.gpu;" ::: "memory");
#pragma unroll 1
            for (int h = lo; h <= hi; h++)
              asm volatile("st.relaxed.gpu.global.u32 [%0], %1;" ::"l"(&g_qflag[slot + h]), "r"((fv >> (2 * h)) & 3) : "memory");
          }
          qm ^= ty == U_QP ? 3 : 1;
        } else {
#pragma unroll 1
          for (int i = 0; i < 4; i++) {
            MW_C(bars + (BAR_QFULL + (i >> 1)) * 8, (qm >> (i >> 1)) & 1);
            if (!(i & 1)) TRACE1(52 + (i >> 1));
            tma_store_2d(&maps.out, br * DM + un.arg() * 256 + i * 64, b * SQ, sbase + OFF_B + i * B_BLK);
          }
          bulk_commit();
          TRACE1(54);
          bulk_wait_read<0>();
          TRACE1(55);
        }
      }
    }
    if (warp == 3 && Unit{units[1]}.bank() && BANK_N > 0) {
      const int line0 = ((Unit{units[1]}.bp() * 2 + rank) * NH + Unit{units[1]}.arg()) * SK * 2;
      const uint32_t bar = bars + BAR_BANK * 8;
      if (elect_one()) mbar_arrive_expect_tx(bar, BANK_N * 4096);
      __nanosleep(BANK_DELAY);
#pragma unroll 1
      for (int i = 0; i < 2 * BANK_N; i++) {
        const int tile = BANK_FIRST + (i >> 1) * (16 - BANK_FIRST) / (BANK_N > 0 ? BANK_N : 1);
        if (elect_one()) tma_2d(sbase + OFF_SINK, (i & 1) ? &maps.vline[br] : &maps.kline[br], 0, line0 + tile * 128, bar);
        __nanosleep(BANK_PACE);
      }
      MW_C(bar, 0);
    }
    __syncwarp();
    if (END_SYNC) cluster_sync();
  } else if (wg == 0) {
    asm volatile("setmaxnreg.inc.sync.aligned.u32 192;");
    ARing r{0, 0};
    uint32_t lph = 0, gph = 0;
    bool opend = false;
    const uint32_t st_off = (16 * warp + (lane & 15)) * 64 + (((lane >> 4) ^ ((lane & 7) >> 1)) << 4);
#pragma unroll 1
    for (int u = 0;; u++) {
      const Unit un{units[u]};
      const int ty = un.type();
      if (ty == U_END) break;
      const bool mc_next = un.mc_next();
      TRACE(u);
      if (ty == U_HQ) {
        r.adv(4);
        if (mc_next) {
          mbar_wait(bars + BAR_GLAST * 8, gph);
          gph ^= 1;
        }
        TRACE(8 + u);
        continue;
      }
      const bool at = ty == U_AT;
      const int n = ty == U_OP ? 64 : 16;
      const int rot = at ? 0 : un.rot();
      float acc0[80], acc1[80];
      if (at && !un.prev_at()) r.adv(3);
      const bool at_end = at && !un.next_at();
      const uint32_t bfull = bars + (at ? BAR_PFULL - 2 : BAR_XFULL) * 8, bempty = bars + (at ? BAR_PEMPTY - 2 : BAR_XEMPTY) * 8;
      uint32_t x = at ? 2 : rot;
      auto mainloop = [&](auto tb) {
        constexpr int TB = decltype(tb)::value;
        constexpr int KB = TB ? 64 : 2;
        PROF(5, mbar_wait(bfull + x * 8, 0));
        PROF(6, mbar_wait(bars + BAR_FO * 8, 0));
        {
          const uint32_t baddr = sbase + OFF_B + (2 + x) * B_BLK;
          const uint64_t da = make_desc(sbase + r.slot * A_SLOT), db = TB ? make_desc_n(baddr) : make_desc(baddr);
          wgmma_fence();
          wgmma_160_init<1, TB>(acc0, da, db);
          wgmma_160_init<1, TB>(acc1, da + 512, db);
#pragma unroll
          for (int kk = 1; kk < 4; kk++) {
            wgmma_160<1, TB>(acc0, da + kk * 128, db + kk * KB);
            wgmma_160<1, TB>(acc1, da + 512 + kk * 128, db + kk * KB);
          }
          wgmma_commit();
        }
        if (TB && opend) {
          fence_async_smem();
          __syncwarp();
          mbar_arrive_n(1, bars + BAR_OSTORE * 8);
        }
#pragma unroll 1
        for (int s = 1; s < n; s++) {
          const uint32_t pslot = r.slot, px = x;
          r.adv((at_end && s >= 14) ? 1 : 2);
          x = at ? 2 + (s & 1) : x_block(s, rot);
          const uint32_t bpar = at ? (s >> 1) & 1 : x_parity(s, rot);
          const uint32_t afull = bars + (BAR_FO + (s & 7)) * 8;
          const bool okb = mbar_test(bfull + x * 8, bpar), oka = mbar_test(afull, (s >> 3) & 1);
          const uint32_t baddr = sbase + OFF_B + (2 + x) * B_BLK;
          const uint64_t da = make_desc(sbase + r.slot * A_SLOT), db = TB ? make_desc_n(baddr) : make_desc(baddr);
          STAMP(128 + (s & 15) * 4);
          PROF(9, wgmma_wait<0>());
          STAMP(128 + (s & 15) * 4 + 1);
          mbar_arrive_n(1, bempty + px * 8);
          release_a(bars, pslot, s + (at ? 3 : 2) < n ? !at : mc_next, peer, 2);
          if (!okb) PROF(7, mbar_wait(bfull + x * 8, bpar));
          if (!oka) PROF(8, mbar_wait(afull, (s >> 3) & 1));
          if (TB ? s == 64 - OP_S_FIRST : (O_LAST && s == 15)) {
            mbar_wait(bars + BAR_GLAST * 8, gph);
            gph ^= 1;
          }
          STAMP(128 + (s & 15) * 4 + 2);
          wgmma_fence();
#pragma unroll
          for (int kk = 0; kk < 4; kk++) {
            wgmma_160<1, TB>(acc0, da + kk * 128, db + kk * KB);
            wgmma_160<1, TB>(acc1, da + 512 + kk * 128, db + kk * KB);
          }
          wgmma_commit();
        }
      };
      if (ty == U_QP) {
        STAMP(128);
        mainloop(Int<0>{});
        wgmma_wait<0>();
        STAMP(129);
        mbar_arrive_n(1, bempty + x * 8);
        release_a(bars, r.slot, mc_next, peer, 2);
        r.adv(2);
        mbar_wait(bars + BAR_XEMPTY * 8, 1);
        store_block_n(acc0, Q_SCALE, sbase + OFF_B + 2 * B_BLK + st_off);
        mbar_wait(bars + (BAR_XEMPTY + 1) * 8, 1);
        store_block_n(acc1, Q_SCALE, sbase + OFF_B + 3 * B_BLK + st_off);
        fence_async_smem();
        __syncwarp();
        mbar_arrive_n(2, bars + (BAR_QFULL + 1) * 8);
        STAMP(130);
      } else {
        mainloop(Int<1>{});
        if (at) {
          const uint32_t blk = 2 * un.qbuf();
          PROF(10, mbar_wait(bars + BAR_LREADY * 8, lph));
          lph ^= 1;
          float* linv = reinterpret_cast<float*>(smem + OFF_LINV);
          bool bad = false;
          if (lane < 20) {
            const int qp = warp * 20 + lane;
            const float2* lsum = reinterpret_cast<const float2*>(smem + OFF_LSUM) + qp;
            float2 l = lsum[0];
#pragma unroll
            for (int w = 1; w < 8; w++) {
              const float2 v = lsum[w * (SQ / 2)];
              l.x += v.x;
              l.y += v.y;
            }
            bad = !(l.x >= 9.094947e-13f && l.x <= 1.0995116e12f && l.y >= 9.094947e-13f && l.y <= 1.0995116e12f);
            *reinterpret_cast<float2*>(linv + (qp & 3) * 40 + (qp >> 2) * 2) = make_float2(__fdividef(1.f, l.x), __fdividef(1.f, l.y));
          }
          uint32_t anybad;
          asm volatile("{\n.reg .pred p, q;\nsetp.ne.b32 p, %1, 0;\nbar.red.or.pred q, 1, 128, p;\nselp.b32 %0, 1, 0, q;\n}\n"
                       : "=r"(anybad) : "r"((uint32_t)bad) : "memory");
          const float4* lv = reinterpret_cast<const float4*>(linv + (lane & 3) * 40);
          float4 iv[10];
#pragma unroll
          for (int i = 0; i < EP_PRE; i++) iv[i] = lv[i];
          STAMP(128);
          wgmma_wait<0>();
          STAMP(129);
          mbar_arrive_n(1, bempty + x * 8);
          mbar_arrive_n(1, bars + BAR_PDONE * 8);
          release_a(bars, r.slot, mc_next, peer, 2);
          r.adv(at_end ? 1 : 2);
          if (!__any_sync(0xffffffffu, anybad)) {
            const uint32_t addr = sbase + OFF_B + blk * B_BLK + st_off;
#pragma unroll
            for (int j = 0; j < 10; j++) {
              if (j == 1) {
#pragma unroll
                for (int i = EP_PRE; i < EP_PRE + 3; i++) iv[i] = lv[i];
              }
              if (j == 2) {
#pragma unroll
                for (int i = EP_PRE + 3; i < 10; i++) iv[i] = lv[i];
              }
              stsm_x4(n_addr(addr, j), pack_bf16(acc0[8 * j] * iv[j].x, acc0[8 * j + 1] * iv[j].y),
                      pack_bf16(acc0[8 * j + 2] * iv[j].x, acc0[8 * j + 3] * iv[j].y),
                      pack_bf16(acc0[8 * j + 4] * iv[j].z, acc0[8 * j + 5] * iv[j].w),
                      pack_bf16(acc0[8 * j + 6] * iv[j].z, acc0[8 * j + 7] * iv[j].w));
              stsm_x4(n_addr(addr, j) + B_BLK, pack_bf16(acc1[8 * j] * iv[j].x, acc1[8 * j + 1] * iv[j].y),
                      pack_bf16(acc1[8 * j + 2] * iv[j].x, acc1[8 * j + 3] * iv[j].y),
                      pack_bf16(acc1[8 * j + 4] * iv[j].z, acc1[8 * j + 5] * iv[j].w),
                      pack_bf16(acc1[8 * j + 6] * iv[j].z, acc1[8 * j + 7] * iv[j].w));
            }
          } else {
            const size_t off = (size_t)((un.bp() * 2 + rank) * NH + un.arg()) * SK * DH;
            slow_attention(smem + OFF_B + blk * B_BLK, ptrs.k[br] + off, ptrs.v[br] + off, warp, lane);
          }
          opend = DEFER_O && un.next_at();
          if (!opend) {
            fence_async_smem();
            __syncwarp();
            mbar_arrive_n(1, bars + BAR_OSTORE * 8);
          }
          STAMP(130);
        } else {
          wgmma_wait<0>();
          mbar_arrive_n(1, bempty + x * 8);
          mbar_wait(bars + BAR_XEMPTY * 8, 1);
          store_block_t(acc0, sbase + OFF_B + 2 * B_BLK, warp, lane);
          mbar_wait(bars + (BAR_XEMPTY + 1) * 8, 1);
          store_block_t(acc1, sbase + OFF_B + 3 * B_BLK, warp, lane);
          fence_async_smem();
          __syncwarp();
          mbar_arrive_n(2, bars + (BAR_QFULL + 1) * 8);
        }
      }
      TRACE(8 + u);
    }
    if (END_SYNC) cluster_sync();
  } else {
    asm volatile("setmaxnreg.inc.sync.aligned.u32 144;");
    const int si = wg - 1;
    ARing r{0, 0};
    uint32_t qm = 0;
    const uint32_t st_off = (16 * warp + (lane & 15)) * 64 + (((lane >> 4) ^ ((lane & 7) >> 1)) << 4);
#pragma unroll 1
    for (int u = 0;; u++) {
      const Unit un{units[u]};
      const int ty = un.type();
      if (ty == U_END) break;
      const bool mc_next = un.mc_next();
      TRACE(16 + si * 16 + u);
      if (ty == U_AT) {
        const uint32_t qb = un.qbuf();
        if (un.qloaded()) qm ^= 1u << qb;
        PROF(12 + 8 * si, mbar_wait(bars + (BAR_QFULL + qb) * 8, ((qm >> qb) & 1) ^ 1));
        const uint64_t dq = make_desc_n(sbase + OFF_B + 2 * qb * B_BLK);
        const uint32_t paddr = sbase + OFF_B + (4 + si) * B_BLK + st_off;
        uint32_t paddr1 = paddr ^ 32;
        asm volatile("" : "+r"(paddr1));
        float l[40];
#pragma unroll
        for (int i = 0; i < 40; i++) l[i] = 0.f;
        if (!un.prev_at()) r.adv(si);
        mbar_wait(bars + (BAR_XEMPTY + 2 + si) * 8, 1);
        bool kok = false;
        if (COLD_STAGGER && si == 1 && !un.prev_at()) {
          const uint32_t c0 = clock();
          while (clock() - c0 < COLD_STAGGER) {}
        }
#pragma unroll 1
        for (int t = 0; t < 8; t++) {
          float acc[80];
          if (!kok) PROF(13 + 8 * si, mbar_wait(bars + (BAR_FS + si + 2 * (t & 1)) * 8, (t >> 1) & 1));
          STAMP((2 * t + si) * 6);
          const uint64_t dk = make_desc(sbase + r.slot * A_SLOT);
          wgmma_fence();
          wgmma_160_init<0, 1>(acc, dk, dq);
#pragma unroll
          for (int kk = 1; kk < 8; kk++)
            wgmma_160<0, 1>(acc, dk + (kk >> 2) * 512 + (kk & 3) * 2, dq + (kk >> 2) * (B_BLK / 16) + (kk & 3) * 64);
          wgmma_commit();
          if (QK_FIRST) mbar_arrive_n(kok ? 1u : 0u, bars + (BAR_PFULL + si) * 8);
          STAMP((2 * t + si) * 6 + 1);
          PROF(14 + 8 * si, wgmma_wait<0>());
          STAMP((2 * t + si) * 6 + 2);
          release_a(bars, r.slot, t == 7 ? mc_next : false, peer, 2);
          r.adv((t == 0 && !un.prev_at()) ? 2 + si : ((t == 7 && !un.next_at()) ? 6 - 2 * si : 4));
          auto expo = [&](int j) {
#pragma unroll
            for (int i = 0; i < 8; i++) acc[8 * j + i] = ex2(acc[8 * j + i]);
          };
          uint32_t pk[40];
          auto reduce = [&](int j) {
            l[4 * j] += acc[8 * j] + acc[8 * j + 2];
            l[4 * j + 1] += acc[8 * j + 1] + acc[8 * j + 3];
            l[4 * j + 2] += acc[8 * j + 4] + acc[8 * j + 6];
            l[4 * j + 3] += acc[8 * j + 5] + acc[8 * j + 7];
#pragma unroll
            for (int i = 0; i < 4; i++) pk[4 * j + i] = pack_bf16(acc[8 * j + 2 * i], acc[8 * j + 2 * i + 1]);
          };
          auto store = [&](int j) { stsm_x4((j & 1 ? paddr1 : paddr) + (j >> 1) * 4096, pk[4 * j], pk[4 * j + 1], pk[4 * j + 2], pk[4 * j + 3]); };
#pragma unroll
          for (int j = 0; j < SM_A; j++) expo(j);
          sched_fence(zero);
#pragma unroll
          for (int j = SM_A; j < SM_B; j++) expo(j);
#pragma unroll
          for (int j = 0; j < SM_A; j++) reduce(j);
          STAMP((2 * t + si) * 6 + 3);
          PROF(15 + 8 * si, mbar_wait(bars + (BAR_PEMPTY + si) * 8, (t & 1) ^ 1));
          STAMP((2 * t + si) * 6 + 4);
#pragma unroll
          for (int j = 0; j < SM_A; j++) store(j);
#pragma unroll
          for (int j = SM_B; j < 10; j++) expo(j);
#pragma unroll
          for (int j = SM_A; j < SM_B; j++) { reduce(j); store(j); }
          if (SM_B < 10) sched_fence(zero);
#pragma unroll
          for (int j = SM_B; j < 10; j++) { reduce(j); store(j); }
          kok = t < 7 && mbar_test(bars + (BAR_FS + si + 2 * ((t + 1) & 1)) * 8, ((t + 1) >> 1) & 1);
          fence_async_smem();
          __syncwarp();
          mbar_arrive_n((QK_FIRST && kok) ? 0u : 1u, bars + (BAR_PFULL + si) * 8);
          STAMP((2 * t + si) * 6 + 5);
        }
        {
          const bool h4 = lane & 16, h3 = lane & 8, h2 = lane & 4;
#pragma unroll
          for (int i = 0; i < 20; i++) {
            const float send = h4 ? l[i] : l[i + 20], keep = h4 ? l[i + 20] : l[i];
            l[i] = keep + __shfl_xor_sync(0xffffffffu, send, 16);
          }
#pragma unroll
          for (int i = 0; i < 10; i++) {
            const float send = h3 ? l[i] : l[i + 10], keep = h3 ? l[i + 10] : l[i];
            l[i] = keep + __shfl_xor_sync(0xffffffffu, send, 8);
          }
#pragma unroll
          for (int i = 0; i < 5; i++) {
            const float send = h2 ? l[i] : l[i + 5], keep = h2 ? l[i + 5] : l[i];
            l[i] = keep + __shfl_xor_sync(0xffffffffu, send, 4);
          }
          float* lsum = reinterpret_cast<float*>(smem + OFF_LSUM) + (si * 4 + warp) * SQ;
          const int i0 = (h4 ? 20 : 0) + (h3 ? 10 : 0) + (h2 ? 5 : 0);
#pragma unroll
          for (int i = 0; i < 5; i++) {
            const int c = i0 + i;
            lsum[8 * (c >> 1) + 2 * (lane & 3) + (c & 1)] = l[i];
          }
          __syncwarp();
          mbar_arrive_n(1, bars + BAR_LREADY * 8);
        }
      } else {
        float acc[80];
        const int n = ty == U_OP ? 64 : 16;
        const int rot = un.rot();
        const bool hq = ty == U_HQ;
        const uint32_t xcnt = hq ? 2 - si : 1, astep = hq ? 1 : 2;
        r.adv(astep - 1);
        uint32_t x = rot;
        auto mainloop = [&](auto tb) {
          constexpr int TB = decltype(tb)::value;
          constexpr int KB = TB ? 64 : 2;
          STAMP(3 * si);
          mbar_wait(bars + (BAR_XFULL + x) * 8, 0);
          mbar_wait(bars + ((hq && un.keep0()) ? BAR_FS : BAR_FG) * 8, 0);
          {
            const uint32_t baddr = sbase + OFF_B + (2 + x) * B_BLK;
            const uint64_t da = make_desc(sbase + r.slot * A_SLOT + si * 8192), db = TB ? make_desc_n(baddr) : make_desc(baddr);
            wgmma_fence();
            wgmma_160_init<1, TB>(acc, da, db);
#pragma unroll
            for (int kk = 1; kk < 4; kk++) wgmma_160<1, TB>(acc, da + kk * 128, db + kk * KB);
            wgmma_commit();
          }
#pragma unroll 1
          for (int s = 1; s < n; s++) {
            const uint32_t pslot = r.slot, px = x;
            r.adv(astep);
            x = x_block(s, rot);
            const uint32_t bpar = x_parity(s, rot);
            const uint32_t afull = bars + (((hq && !(s & 4) == un.keep0()) ? BAR_FS : BAR_FG) + (s & 3)) * 8, apar = (s >> (hq ? 3 : 2)) & 1;
            const bool okb = mbar_test(bars + (BAR_XFULL + x) * 8, bpar), oka = mbar_test(afull, apar);
            const uint32_t baddr = sbase + OFF_B + (2 + x) * B_BLK;
            const uint64_t da = make_desc(sbase + r.slot * A_SLOT + si * 8192), db = TB ? make_desc_n(baddr) : make_desc(baddr);
            STAMP((s & 15) * 6 + 3 * si);
            PROF(18 + 8 * si, wgmma_wait<0>());
            STAMP((s & 15) * 6 + 3 * si + 1);
            mbar_arrive_n(xcnt, bars + (BAR_XEMPTY + px) * 8);
            release_a(bars, pslot, astep * s - 1 + NA < astep * n ? true : mc_next, peer, 1);
            if (!okb) PROF(16 + 8 * si, mbar_wait(bars + (BAR_XFULL + x) * 8, bpar));
            if (!oka) PROF(17 + 8 * si, mbar_wait(afull, apar));
            STAMP((s & 15) * 6 + 3 * si + 2);
            wgmma_fence();
#pragma unroll
            for (int kk = 0; kk < 4; kk++) wgmma_160<1, TB>(acc, da + kk * 128, db + kk * KB);
            wgmma_commit();
          }
          mbar_arrive_n((TB || (hq ? mc_next : O_LAST)) ? 1u : 0u, bars + BAR_GLAST * 8);
          wgmma_wait<0>();
          mbar_arrive_n(xcnt, bars + (BAR_XEMPTY + x) * 8);
          release_a(bars, r.slot, mc_next, peer, 1);
          r.adv(1);
          STAMP(3 * si + 1);
          PROF(19 + 8 * si, mbar_wait(bars + BAR_QEMPTY * 8, (qm & 1) ^ 1));
        };
        if (ty != U_OP) {
          mainloop(Int<0>{});
          store_block_n(acc, Q_SCALE, sbase + OFF_B + si * B_BLK + st_off);
        } else {
          mainloop(Int<1>{});
          store_block_t(acc, sbase + OFF_B + si * B_BLK, warp, lane);
        }
        fence_async_smem();
        __syncwarp();
        mbar_arrive_n(1, bars + BAR_QFULL * 8);
        STAMP(3 * si + 2);
        qm ^= hq ? 1 : 3;
      }
      TRACE(24 + si * 16 + u);
    }
    if (END_SYNC) cluster_sync();
  }
}

typedef CUresult (*EncodeFn)(CUtensorMap*, CUtensorMapDataType, cuuint32_t, void*, const cuuint64_t*, const cuuint64_t*,
                             const cuuint32_t*, const cuuint32_t*, CUtensorMapInterleave, CUtensorMapSwizzle,
                             CUtensorMapL2promotion, CUtensorMapFloatOOBfill);

void make_map_2d(EncodeFn enc, CUtensorMap* m, const void* p, uint64_t cols, uint64_t rows, uint32_t box_rows,
                 CUtensorMapL2promotion promo = W_PROMO) {
  cuuint64_t dims[2] = {cols, rows}, strides[1] = {cols * 2};
  cuuint32_t box[2] = {64, box_rows}, es[2] = {1, 1};
  enc(m, CU_TENSOR_MAP_DATA_TYPE_BFLOAT16, 2, const_cast<void*>(p), dims, strides, box, es, CU_TENSOR_MAP_INTERLEAVE_NONE,
      CU_TENSOR_MAP_SWIZZLE_128B, promo, CU_TENSOR_MAP_FLOAT_OOB_FILL_NONE);
}
void make_map_kv(EncodeFn enc, CUtensorMap* m, const void* p) {
  cuuint64_t dims[3] = {64, (cuuint64_t)NB * NH * SK, 2}, strides[2] = {DH * 2, 128};
  cuuint32_t box[3] = {64, 64, 2}, es[3] = {1, 1, 1};
  enc(m, CU_TENSOR_MAP_DATA_TYPE_BFLOAT16, 3, const_cast<void*>(p), dims, strides, box, es, CU_TENSOR_MAP_INTERLEAVE_NONE,
      CU_TENSOR_MAP_SWIZZLE_128B, KV_PROMO, CU_TENSOR_MAP_FLOAT_OOB_FILL_NONE);
}

void make_map_lines(EncodeFn enc, CUtensorMap* m, const void* p) {
  cuuint64_t dims[2] = {64, (cuuint64_t)NB * NH * SK * 2}, strides[1] = {128};
  cuuint32_t box[2] = {8, 128}, es[2] = {1, 1};
  enc(m, CU_TENSOR_MAP_DATA_TYPE_BFLOAT16, 2, const_cast<void*>(p), dims, strides, box, es, CU_TENSOR_MAP_INTERLEAVE_NONE,
      CU_TENSOR_MAP_SWIZZLE_NONE, CU_TENSOR_MAP_L2_PROMOTION_L2_128B, CU_TENSOR_MAP_FLOAT_OOB_FILL_NONE);
}

void make_plan(Plan* p, bool spare) {
  struct U { int type, arg, bp, flags; };
  enum { F_QBUF1 = 1 << 10, F_LOAD = 1 << 11, F_KEEP0 = 1 << 12, F_BANK = 1 << 13, F_KEEP1 = 1 << 17 };
  float done[NH] = {};
  for (int r = 0; r < MAX_ROLES; r++) {
    U u[MAX_UNITS];
    int n = 0;
    const int bp = r >> 3, i = (r & 7) >> 1;
    if (r == 32) {
      for (int k = 0; k < 4; k++) u[n++] = {U_AT, 12, k, F_LOAD | ((k & 1) ? F_QBUF1 : 0)};
    } else if (r & 1) {
      auto head = [&](int j, int g, int which) { return 2 * (4 + 4 * j + g) + which; };
      const int m = i >> 1, w = i & 1;
      int h[7] = {i, head(0, m, w), head(1, m, w), head(2, m, w), head(0, m + 2, w), head(1, m + 2, w), head(2, m + 2, w)};
      if (G2_LATE_HQ && w == 0) {
        if (!(spare && m == 0)) h[3] = h[4];
        h[4] = h[5]; h[5] = 4 + m;
      }
      u[n++] = {U_HQ, i, bp, F_KEEP0};
      for (int k = 0; k < 7; k++) u[n++] = {U_AT, h[k], bp, (k ? F_LOAD : 0) | ((k & 1) ? F_QBUF1 : 0)};
    } else if (i < 2) {
      for (int j = 0; j < 3; j++) u[n++] = {U_QP, 4 + 4 * j + i, bp, (G2_LATE_HQ && j == 2 && !(spare && i == 0)) ? F_KEEP0 : 0};
      if (spare) {
        u[n++] = i == 0 ? U{U_QP, 2, bp, 0} : U{U_AT, 26, bp, 0};
      } else if (G2_LATE_HQ) {
        u[n++] = {U_AT, 2 * (12 + i), bp, 0};
        u[n++] = {U_HQ, 4 + i, bp, 0};
      } else {
        u[n++] = {U_HQ, 4 + i, bp, F_KEEP0};
        u[n++] = {U_AT, 4 + i, bp, 0};
      }
      u[n++] = {U_OP, i, bp, 0};
    } else {
      u[n++] = {U_HQ, 4 + i, bp, F_KEEP0};
      u[n++] = {U_AT, 4 + i, bp, F_BANK};
      for (int j = 0; j < 3; j++) u[n++] = {U_QP, 4 + 4 * j + i, bp, 0};
      u[n++] = {U_OP, i, bp, 0};
    }
    float t = r == 32 ? 3.0f : 0.f;
    for (int k = 0; k < MAX_UNITS; k++) {
      if (k >= n) { p->unit[r][k] = U_END; continue; }
      const bool prev_at = k > 0 && u[k - 1].type == U_AT;
      uint32_t d = u[k].type | (u[k].arg << 3) | (u[k].bp << 8) | u[k].flags;
      if (u[k].type != U_AT && k > 0 && u[k - 1].type == U_QP) d |= 1u << 14;
      if (prev_at) d |= 1u << 15;
      if (k + 1 < n) d |= 1u << (u[k + 1].type != U_AT ? 16 : 18);
      p->unit[r][k] = d;
      t += u[k].type == U_HQ ? 0.6f : 1.f;
      if (u[k].type == U_AT && (r < 32 || spare)) done[u[k].arg] = std::max(done[u[k].arg], t + 0.001f * u[k].arg);
    }
  }
  for (int h = 0; h < NH; h++) {
    int rank = 0;
    for (int g = 0; g < NH; g++) rank += done[g] < done[h];
    p->op_head[rank] = (uint8_t)h;
  }
}

}

extern "C" void kernel_launch(void* const* d_in, const int* in_sizes, int n_in, void* d_out, int out_size) {
  (void)in_sizes; (void)n_in; (void)out_size;
  void* fn = nullptr;
  cudaDriverEntryPointQueryResult qr;
  cudaGetDriverEntryPoint("cuTensorMapEncodeTiled", &fn, cudaEnableDefault, &qr);
  EncodeFn enc = reinterpret_cast<EncodeFn>(fn);
  Maps maps;
  Ptrs ptrs;
  for (int br = 0; br < 2; br++) {
    void* const* in = d_in + 5 * br;
    make_map_2d(enc, &maps.x[br], in[0], DM, NB * SQ, SQ, X_PROMO);
    make_map_kv(enc, &maps.k[br], in[1]);
    make_map_kv(enc, &maps.v[br], in[2]);
    make_map_lines(enc, &maps.kline[br], in[1]);
    make_map_lines(enc, &maps.vline[br], in[2]);
    make_map_2d(enc, &maps.wq[br], in[3], NH * DH, DM, 64);
    make_map_2d(enc, &maps.wo[br], in[4], DM, NH * DH, 64);
    ptrs.k[br] = static_cast<const __nv_bfloat16*>(in[1]);
    ptrs.v[br] = static_cast<const __nv_bfloat16*>(in[2]);
  }
  make_map_2d(enc, &maps.out, d_out, 2 * DM, NB * SQ, SQ);
  cudaFuncSetAttribute(mha2_kernel, cudaFuncAttributeMaxDynamicSharedMemorySize, SMEM_BYTES);
  cudaLaunchConfig_t cfg = {};
  cfg.gridDim = 132;
  cfg.blockDim = 512;
  cfg.dynamicSmemBytes = SMEM_BYTES;
  int ncl = 0;
  cudaOccupancyMaxActiveClusters(&ncl, mha2_kernel, &cfg);
  ncl = (USE_E && ncl >= 66) ? 66 : 64;
  Plan plan;
  make_plan(&plan, ncl == 66);
  mha2_kernel<<<2 * ncl, 512, SMEM_BYTES, cudaStreamPerThread>>>(maps, ptrs, plan);
}
```

```cpp
#include <cuda_runtime.h>
#include <cuda_bf16.h>
#include <cuda.h>
#include <stdint.h>
#include <string.h>
#include <algorithm>

namespace {

constexpr int SQ = 160, DM = 1024, NH = 32, SK = 1024, DH = 128, NB = 8;
constexpr int A_SLOT = 16384, NA = 6;
constexpr int B_BLK = 20480;
constexpr int OFF_B = NA * A_SLOT;
constexpr int OFF_LSUM = OFF_B + 6 * B_BLK;
constexpr int OFF_LINV = OFF_LSUM + 8 * SQ * 4;
constexpr int OFF_BAR = OFF_LINV + SQ * 4;
constexpr int OFF_SINK = OFF_BAR + 640 + 1024;
constexpr int SMEM_BYTES = OFF_SINK + 2048 + 1024;
constexpr int BAR_FO = 47, BAR_FG = 41, BAR_BANK = 45, BAR_GLAST = 46, BAR_ORD = 55, BAR_FS = 0, BAR_AEMPTY = 6, BAR_XFULL = 12, BAR_XEMPTY = 16, BAR_PFULL = 20, BAR_PEMPTY = 22,
              BAR_QFULL = 24, BAR_QEMPTY = 26, BAR_LREADY = 28, BAR_OSTORE = 29, BAR_PDONE = 30,
              BAR_REMPTY = 31;
constexpr float Q_SCALE = 0.08838834764831845f * 1.4426950408889634f;
constexpr uint32_t SPIN_LIMIT = 1u << 26;

#define KV_PROMO CU_TENSOR_MAP_L2_PROMOTION_L2_128B
#define X_PROMO CU_TENSOR_MAP_L2_PROMOTION_L2_128B
#define W_PROMO CU_TENSOR_MAP_L2_PROMOTION_L2_128B

#define JSTAR 3
#define E_SHIFT 0
#define OP_GATE 24
#define USE_E 1
#define QK_FIRST 1
#define SLEEP_MASK 6
#define MW_A(b, p) ((SLEEP_MASK & 1) ? mbar_wait_sleep(b, p) : mbar_wait(b, p))
#define MW_B(b, p) ((SLEEP_MASK & 2) ? mbar_wait_sleep(b, p) : mbar_wait(b, p))
#define MW_C(b, p) ((SLEEP_MASK & 4) ? mbar_wait_sleep(b, p) : mbar_wait(b, p))
#define EP_PRE 4
#define DEFER_O 1
#define G2_LATE_HQ 1
#define WQ_EF 1
#define WO_EF 0
#define OP_S_FIRST 2
#define COLD_STAGGER 250
#define END_SYNC 0
#define DYN 4
#define X_LATE 1
#define O_LAST 0
#define ST_PACE 0
#define ST_SLEEP 0
#define G2_DELAY 0
#define STAG1 15
#define STAG2 0
#define STAG3 0
#define PLAN_G0 "qqqqo"
#define PLAN_G1 "qqQao"
#define PLAN_G2 "Qaqqo"
#define PLAN_G3 "Qaqqo"
#define PLAN_A0 "haaaaaaa"
#define PLAN_A1 "haaaaaaa"
#define PLAN_A2 "Kbaaaaaa"
#define PLAN_A3 "Kbaaaaaa"
#define E_START 3.0f
#define E_DELAY 260
#define STAG0 0
#define GD0 0
#define GD1 34
#define GD2 0
#define GD3 0
#define L_EARLY 2
#define BANK_N 12
#define BANK_FIRST 3
#define BANK_DELAY 1500
#define BANK_PACE 330
#define PROBE_REP 2
#define W_EF 1

#define SM_A 4
#define SM_B 7

#define WAIT_HINT 0

#define SIDE_AWARE 1
#define LOCAL_SCRATCH 1

struct Maps {
  CUtensorMap x[2], wq[2], wo[2], k[2], v[2], kline[2], vline[2], out;
};
struct Ptrs {
  const __nv_bfloat16* k[2];
  const __nv_bfloat16* v[2];
};

constexpr int PAGE = 2 << 20, SLOTS_PER_PAGE = 25, SLOT_SPAN = 81920, PROBE_OFF = SLOTS_PER_PAGE * SLOT_SPAN;
constexpr uint32_t PART_MASK = (1u << 13) | (1u << 16) | (1u << 17) | (1u << 19);
__device__ uint4 g_scratch[22 * (PAGE / 16)];
__device__ uint32_t g_claim, g_claim_done;
__device__ __align__(16) uint32_t g_qflag[2 * NB * NH];
__device__ uint4 g_oflag[2 * NB * NH];

__device__ __forceinline__ uint32_t smem_u32(const void* p) { return (uint32_t)__cvta_generic_to_shared(p); }
__device__ __forceinline__ bool elect_one() {
  uint32_t p;
  asm volatile("{\n.reg .pred p;\nelect.sync _|p, 0xffffffff;\nselp.b32 %0, 1, 0, p;\n}\n" : "=r"(p));
  return p;
}
__device__ __forceinline__ void mbar_init(uint32_t bar, uint32_t cnt) {
  asm volatile("mbarrier.init.shared::cta.b64 [%0], %1;" ::"r"(bar), "r"(cnt));
}
__device__ __forceinline__ void mbar_arrive_expect_tx(uint32_t bar, uint32_t bytes) {
  asm volatile("mbarrier.arrive.expect_tx.shared::cta.b64 _, [%0], %1;" ::"r"(bar), "r"(bytes) : "memory");
}
__device__ __forceinline__ void mbar_expect_tx(uint32_t bar, uint32_t bytes) {
  asm volatile("mbarrier.expect_tx.relaxed.cta.shared::cta.b64 [%0], %1;" ::"r"(bar), "r"(bytes) : "memory");
}
__device__ __forceinline__ void mbar_arrive(uint32_t bar, uint32_t cnt) {
  asm volatile("mbarrier.arrive.shared::cta.b64 _, [%0], %1;" ::"r"(bar), "r"(cnt) : "memory");
}
__device__ __forceinline__ void mbar_arrive_n(uint32_t n, uint32_t bar) {
  asm volatile("{\n.reg .pred p;\n.reg .b32 l;\nmov.u32 l, %%laneid;\nsetp.lt.u32 p, l, %1;\n"
               "@p mbarrier.arrive.shared::cta.b64 _, [%0];\n}\n" ::"r"(bar), "r"(n) : "memory");
}
__device__ __forceinline__ void mbar_arrive_remote_n(uint32_t n, uint32_t bar, uint32_t cta) {
  asm volatile(
      "{\n.reg .pred p;\n.reg .b32 ra, l;\nmov.u32 l, %%laneid;\nsetp.lt.u32 p, l, %2;\nmapa.shared::cluster.u32 ra, %0, %1;\n"
      "@p mbarrier.arrive.shared::cluster.b64 _, [ra];\n}\n" ::"r"(bar), "r"(cta), "r"(n) : "memory");
}
__device__ __forceinline__ void mbar_wait(uint32_t bar, uint32_t parity) {
  asm volatile(
      "{\n.reg .pred p;\n.reg .b32 n;\nmov.b32 n, 0;\n"
      "WAIT_%=:\n"
      "mbarrier.try_wait.parity.shared::cta.b64 p, [%0], %1;\n"
      "@p bra DONE_%=;\n"
      "add.u32 n, n, 1;\n"
      "setp.lt.u32 p, n, %2;\n"
      "@p bra WAIT_%=;\n"
      "trap;\n"
      "DONE_%=:\n}\n" ::"r"(bar), "r"(parity), "n"(SPIN_LIMIT), "n"(WAIT_HINT) : "memory");
}
__device__ __forceinline__ void mbar_wait_sleep(uint32_t bar, uint32_t parity) {
  asm volatile(
      "{\n.reg .pred p;\n.reg .b32 n;\nmov.b32 n, 0;\n"
      "WAIT_%=:\n"
      "mbarrier.try_wait.parity.shared::cta.b64 p, [%0], %1, %3;\n"
      "@p bra DONE_%=;\n"
      "add.u32 n, n, 1;\n"
      "setp.lt.u32 p, n, %2;\n"
      "@p bra WAIT_%=;\n"
      "trap;\n"
      "DONE_%=:\n}\n" ::"r"(bar), "r"(parity), "n"(SPIN_LIMIT >> 4), "n"(4000) : "memory");
}
__device__ __forceinline__ bool mbar_test(uint32_t bar, uint32_t parity) {
  uint32_t ok;
  asm volatile("{\n.reg .pred p;\nmbarrier.test_wait.parity.shared::cta.b64 p, [%1], %2;\nselp.b32 %0, 1, 0, p;\n}\n"
               : "=r"(ok) : "r"(bar), "r"(parity) : "memory");
  return ok;
}
__device__ __forceinline__ void tma_prefetch_2d(const CUtensorMap* m, int c0, int c1) {
  asm volatile("cp.async.bulk.prefetch.tensor.2d.L2.global [%0, {%1, %2}];" ::"l"(m), "r"(c0), "r"(c1) : "memory");
}
__device__ __forceinline__ void tma_2d(uint32_t dst, const CUtensorMap* m, int c0, int c1, uint32_t bar) {
  asm volatile(
      "cp.async.bulk.tensor.2d.shared::cluster.global.mbarrier::complete_tx::bytes [%0], [%1, {%3, %4}], [%2];" ::"r"(dst),
      "l"(m), "r"(bar), "r"(c0), "r"(c1) : "memory");
}
__device__ __forceinline__ void tma_2d_mc(uint32_t dst, const CUtensorMap* m, int c0, int c1, uint32_t bar, uint64_t pol) {
  asm volatile(
      "cp.async.bulk.tensor.2d.shared::cluster.global.mbarrier::complete_tx::bytes.multicast::cluster.L2::cache_hint"
      " [%0], [%1, {%3, %4}], [%2], %5, %6;" ::"r"(dst), "l"(m), "r"(bar), "r"(c0), "r"(c1), "h"((uint16_t)3), "l"(pol) : "memory");
}
__device__ __forceinline__ void tma_3d_hint(uint32_t dst, const CUtensorMap* m, int c1, uint32_t bar, uint64_t pol) {
  asm volatile(
      "cp.async.bulk.tensor.3d.shared::cluster.global.mbarrier::complete_tx::bytes.L2::cache_hint"
      " [%0], [%1, {%4, %3, %4}], [%2], %5;" ::"r"(dst), "l"(m), "r"(bar), "r"(c1), "r"(0), "l"(pol) : "memory");
}
__device__ __forceinline__ void tma_store_2d(const CUtensorMap* m, int c0, int c1, uint32_t src) {
  asm volatile("cp.async.bulk.tensor.2d.global.shared::cta.bulk_group [%0, {%2, %3}], [%1];" ::"l"(m), "r"(src), "r"(c0),
               "r"(c1) : "memory");
}
__device__ __forceinline__ void bulk_g2s(uint32_t dst, const void* src, uint32_t bytes, uint32_t bar) {
  asm volatile("cp.async.bulk.shared::cluster.global.mbarrier::complete_tx::bytes [%0], [%1], %2, [%3];" ::"r"(dst),
               "l"(src), "r"(bytes), "r"(bar) : "memory");
}
__device__ __forceinline__ void bulk_s2g(void* dst, uint32_t src, uint32_t bytes) {
  asm volatile("cp.async.bulk.global.shared::cta.bulk_group [%0], [%1], %2;" ::"l"(dst), "r"(src), "r"(bytes) : "memory");
}
__device__ __forceinline__ void bulk_prefetch(const void* src, uint32_t bytes, uint64_t pol) {
  asm volatile("cp.async.bulk.prefetch.L2.global.L2::cache_hint [%0], %1, %2;" ::"l"(src), "r"(bytes), "l"(pol) : "memory");
}
__device__ __forceinline__ void bulk_prefetch(const void* src, uint32_t bytes) {
  asm volatile("cp.async.bulk.prefetch.L2.global [%0], %1;" ::"l"(src), "r"(bytes) : "memory");
}
__device__ __forceinline__ void bulk_commit() { asm volatile("cp.async.bulk.commit_group;" ::: "memory"); }
template <int N> __device__ __forceinline__ void bulk_wait_read() { asm volatile("cp.async.bulk.wait_group.read %0;" ::"n"(N) : "memory"); }
template <int N> __device__ __forceinline__ void bulk_wait() { asm volatile("cp.async.bulk.wait_group %0;" ::"n"(N) : "memory"); }
__device__ __forceinline__ void fence_async_smem() { asm volatile("fence.proxy.async.shared::cta;" ::: "memory"); }
__device__ __forceinline__ void fence_async_global() { asm volatile("fence.proxy.async.global;" ::: "memory"); }
__device__ __forceinline__ void wgmma_fence() { asm volatile("wgmma.fence.sync.aligned;" ::: "memory"); }
__device__ __forceinline__ void wgmma_commit() { asm volatile("wgmma.commit_group.sync.aligned;" ::: "memory"); }
template <int N> __device__ __forceinline__ void wgmma_wait() { asm volatile("wgmma.wait_group.sync.aligned %0;" ::"n"(N) : "memory"); }
__device__ __forceinline__ void cluster_sync() {
  asm volatile("barrier.cluster.arrive.relaxed;\nbarrier.cluster.wait;" ::: "memory");
}
__device__ __forceinline__ uint64_t make_desc(uint32_t addr) {
  return (uint64_t)((addr & 0x3FFFF) >> 4) | ((uint64_t)1 << 16) | ((uint64_t)64 << 32) | ((uint64_t)1 << 62);
}
__device__ __forceinline__ uint64_t make_desc_n(uint32_t addr) {
  return (uint64_t)((addr & 0x3FFFF) >> 4) | ((uint64_t)256 << 16) | ((uint64_t)32 << 32) | ((uint64_t)2 << 62);
}
__device__ __forceinline__ float ex2(float x) {
  float y;
  asm volatile("ex2.approx.ftz.f32 %0, %1;" : "=f"(y) : "f"(x));
  return y;
}
__device__ __forceinline__ void sched_fence(uint32_t zero) {
  asm volatile("{\n.reg .pred p;\nsetp.eq.b32 p, %0, 0;\nFENCE_%=:\n@p bra.uni FDONE_%=;\nnanosleep.u32 1;\nbra.uni FENCE_%=;\nFDONE_%=:\n}\n" ::"r"(zero) : "memory");
}
__device__ __forceinline__ uint32_t pack_bf16(float lo, float hi) {
  uint32_t r;
  asm("cvt.rn.bf16x2.f32 %0, %1, %2;" : "=r"(r) : "f"(hi), "f"(lo));
  return r;
}
__device__ __forceinline__ void stsm_x4_t(uint32_t addr, uint32_t r0, uint32_t r1, uint32_t r2, uint32_t r3) {
  asm volatile("stmatrix.sync.aligned.m8n8.x4.trans.shared.b16 [%0], {%1, %2, %3, %4};" ::"r"(addr), "r"(r0), "r"(r1),
               "r"(r2), "r"(r3) : "memory");
}
__device__ __forceinline__ void stsm_x4(uint32_t addr, uint32_t r0, uint32_t r1, uint32_t r2, uint32_t r3) {
  asm volatile("stmatrix.sync.aligned.m8n8.x4.shared.b16 [%0], {%1, %2, %3, %4};" ::"r"(addr), "r"(r0), "r"(r1), "r"(r2),
               "r"(r3) : "memory");
}
__device__ __forceinline__ uint32_t wait_flag(const uint32_t* f) {
  uint32_t v, n = 0;
  while (true) {
    asm volatile("ld.acquire.gpu.global.u32 %0, [%1];" : "=r"(v) : "l"(f) : "memory");
    if (v) break;
    if (++n > (SPIN_LIMIT >> 2)) __trap();
    __nanosleep(32);
  }
  fence_async_global();
  return __shfl_sync(0xffffffffu, v, 0);
}

__device__ __forceinline__ uint8_t* scratch_base() {
  return reinterpret_cast<uint8_t*>((reinterpret_cast<uintptr_t>(g_scratch) + PAGE - 1) & ~(uintptr_t)(PAGE - 1));
}
__device__ __forceinline__ uint32_t slot_off(uint32_t slot) {
  return (slot / SLOTS_PER_PAGE) * PAGE + (slot % SLOTS_PER_PAGE) * SLOT_SPAN;
}
__device__ __forceinline__ uint32_t piece_off(uint32_t off, uint32_t sel) {
  return off + (((__popc(off & PART_MASK) ^ sel) & 1) << 12);
}
__device__ __forceinline__ uint32_t local_selector(uint8_t* page, uint32_t pair, uint32_t id, int lane) {
  const uint32_t off = PROBE_OFF + pair * 8192;
  uint8_t *p0 = page + piece_off(off, 0) + id * 32, *p1 = page + piece_off(off, 1) + id * 32;
  if (lane < 4) asm volatile("st.global.v4.u32 [%0], {0, 0, 0, 0};" ::"l"((lane & 2 ? p1 : p0) + (lane & 1) * 16) : "memory");
  __syncwarp();
  uint32_t t1 = 0, t2 = 0;
  if (lane == 0)
    asm volatile(
        "{\n.reg .b32 a, b;\n"
        "atom.relaxed.gpu.global.exch.b32 a, [%2], 1;\natom.relaxed.gpu.global.exch.b32 b, [%3], 1;\n"
        "{\n.reg .pred p;\nsetp.eq.u32 p, a, 0xffffffff;\n@p trap;\n}\n"
        "mov.u32 %0, %%clock;\n"
        "{\n.reg .pred p;\nsetp.eq.u32 p, b, 0xffffffff;\n@p trap;\n}\n"
        "mov.u32 %1, %%clock;\n}\n"
        : "=r"(t1), "=r"(t2) : "l"(p0), "l"(p1) : "memory");
  return __shfl_sync(0xffffffffu, t2 - t1 > 100 ? 0u : 1u, 0);
}

template <int TA, int TB>
__device__ __forceinline__ void wgmma_160(float (&d)[80], uint64_t descA, uint64_t descB) {
  asm volatile(
      "wgmma.mma_async.sync.aligned.m64n160k16.f32.bf16.bf16 {"
      "%0, %1, %2, %3, %4, %5, %6, %7, %8, %9, %10, %11, %12, %13, %14, %15, "
      "%16, %17, %18, %19, %20, %21, %22, %23, %24, %25, %26, %27, %28, %29, %30, %31, "
      "%32, %33, %34, %35, %36, %37, %38, %39, %40, %41, %42, %43, %44, %45, %46, %47, "
      "%48, %49, %50, %51, %52, %53, %54, %55, %56, %57, %58, %59, %60, %61, %62, %63, "
      "%64, %65, %66, %67, %68, %69, %70, %71, %72, %73, %74, %75, %76, %77, %78, %79}, "
      "%80, %81, 1, 1, 1, %82, %83;\n"
      : "+f"(d[0]), "+f"(d[1]), "+f"(d[2]), "+f"(d[3]), "+f"(d[4]), "+f"(d[5]), "+f"(d[6]), "+f"(d[7]),
        "+f"(d[8]), "+f"(d[9]), "+f"(d[10]), "+f"(d[11]), "+f"(d[12]), "+f"(d[13]), "+f"(d[14]), "+f"(d[15]),
        "+f"(d[16]), "+f"(d[17]), "+f"(d[18]), "+f"(d[19]), "+f"(d[20]), "+f"(d[21]), "+f"(d[22]), "+f"(d[23]),
        "+f"(d[24]), "+f"(d[25]), "+f"(d[26]), "+f"(d[27]), "+f"(d[28]), "+f"(d[29]), "+f"(d[30]), "+f"(d[31]),
        "+f"(d[32]), "+f"(d[33]), "+f"(d[34]), "+f"(d[35]), "+f"(d[36]), "+f"(d[37]), "+f"(d[38]), "+f"(d[39]),
        "+f"(d[40]), "+f"(d[41]), "+f"(d[42]), "+f"(d[43]), "+f"(d[44]), "+f"(d[45]), "+f"(d[46]), "+f"(d[47]),
        "+f"(d[48]), "+f"(d[49]), "+f"(d[50]), "+f"(d[51]), "+f"(d[52]), "+f"(d[53]), "+f"(d[54]), "+f"(d[55]),
        "+f"(d[56]), "+f"(d[57]), "+f"(d[58]), "+f"(d[59]), "+f"(d[60]), "+f"(d[61]), "+f"(d[62]), "+f"(d[63]),
        "+f"(d[64]), "+f"(d[65]), "+f"(d[66]), "+f"(d[67]), "+f"(d[68]), "+f"(d[69]), "+f"(d[70]), "+f"(d[71]),
        "+f"(d[72]), "+f"(d[73]), "+f"(d[74]), "+f"(d[75]), "+f"(d[76]), "+f"(d[77]), "+f"(d[78]), "+f"(d[79])
      : "l"(descA), "l"(descB), "n"(TA), "n"(TB));
}
template <int TA, int TB>
__device__ __forceinline__ void wgmma_160_init(float (&d)[80], uint64_t descA, uint64_t descB) {
  asm volatile(
      "wgmma.mma_async.sync.aligned.m64n160k16.f32.bf16.bf16 {"
      "%0, %1, %2, %3, %4, %5, %6, %7, %8, %9, %10, %11, %12, %13, %14, %15, "
      "%16, %17, %18, %19, %20, %21, %22, %23, %24, %25, %26, %27, %28, %29, %30, %31, "
      "%32, %33, %34, %35, %36, %37, %38, %39, %40, %41, %42, %43, %44, %45, %46, %47, "
      "%48, %49, %50, %51, %52, %53, %54, %55, %56, %57, %58, %59, %60, %61, %62, %63, "
      "%64, %65, %66, %67, %68, %69, %70, %71, %72, %73, %74, %75, %76, %77, %78, %79}, "
      "%80, %81, 0, 1, 1, %82, %83;\n"
      : "=f"(d[0]), "=f"(d[1]), "=f"(d[2]), "=f"(d[3]), "=f"(d[4]), "=f"(d[5]), "=f"(d[6]), "=f"(d[7]),
        "=f"(d[8]), "=f"(d[9]), "=f"(d[10]), "=f"(d[11]), "=f"(d[12]), "=f"(d[13]), "=f"(d[14]), "=f"(d[15]),
        "=f"(d[16]), "=f"(d[17]), "=f"(d[18]), "=f"(d[19]), "=f"(d[20]), "=f"(d[21]), "=f"(d[22]), "=f"(d[23]),
        "=f"(d[24]), "=f"(d[25]), "=f"(d[26]), "=f"(d[27]), "=f"(d[28]), "=f"(d[29]), "=f"(d[30]), "=f"(d[31]),
        "=f"(d[32]), "=f"(d[33]), "=f"(d[34]), "=f"(d[35]), "=f"(d[36]), "=f"(d[37]), "=f"(d[38]), "=f"(d[39]),
        "=f"(d[40]), "=f"(d[41]), "=f"(d[42]), "=f"(d[43]), "=f"(d[44]), "=f"(d[45]), "=f"(d[46]), "=f"(d[47]),
        "=f"(d[48]), "=f"(d[49]), "=f"(d[50]), "=f"(d[51]), "=f"(d[52]), "=f"(d[53]), "=f"(d[54]), "=f"(d[55]),
        "=f"(d[56]), "=f"(d[57]), "=f"(d[58]), "=f"(d[59]), "=f"(d[60]), "=f"(d[61]), "=f"(d[62]), "=f"(d[63]),
        "=f"(d[64]), "=f"(d[65]), "=f"(d[66]), "=f"(d[67]), "=f"(d[68]), "=f"(d[69]), "=f"(d[70]), "=f"(d[71]),
        "=f"(d[72]), "=f"(d[73]), "=f"(d[74]), "=f"(d[75]), "=f"(d[76]), "=f"(d[77]), "=f"(d[78]), "=f"(d[79])
      : "l"(descA), "l"(descB), "n"(TA), "n"(TB));
}

enum { U_QP = 0, U_AT = 1, U_OP = 2, U_HQ = 3, U_END = 4 };
constexpr int MAX_UNITS = 9, MAX_ROLES = 33;
struct Plan {
  uint32_t unit[MAX_ROLES][MAX_UNITS];
  uint8_t op_head[NH];
};
struct Unit {
  uint32_t d;
  __device__ __forceinline__ int type() const { return d & 7; }
  __device__ __forceinline__ int arg() const { return (d >> 3) & 31; }
  __device__ __forceinline__ int bp() const { return (d >> 8) & 3; }
  __device__ __forceinline__ int qbuf() const { return (d >> 10) & 1; }
  __device__ __forceinline__ bool qloaded() const { return (d >> 11) & 1; }
  __device__ __forceinline__ bool keep0() const { return (d >> 12) & 1; }
  __device__ __forceinline__ bool keep1() const { return (d >> 17) & 1; }
  __device__ __forceinline__ bool bank() const { return (d >> 13) & 1; }
  __device__ __forceinline__ int rot() const { return (d >> 13) & 2; }
  __device__ __forceinline__ bool prev_at() const { return (d >> 15) & 1; }
  __device__ __forceinline__ bool next_at() const { return (d >> 18) & 1; }
  __device__ __forceinline__ bool mc_next() const { return (d >> 16) & 1; }
};

__device__ __forceinline__ uint32_t x_block(int s, int rot) {
  return (X_LATE && rot && s < 16) ? (0x44e4e4eeu >> (2 * s)) & 3 : (s + rot) & 3;
}
__device__ __forceinline__ uint32_t x_parity(int s, int rot) {
  return (X_LATE && rot && s < 16) ? (0xcf0cu >> s) & 1 : (s >> 2) & 1;
}

template <int V> struct Int { static constexpr int value = V; };

struct ARing {
  uint32_t slot, phase;
  __device__ __forceinline__ void adv(uint32_t n) {
    slot += n;
    if (slot >= NA) { slot -= NA; phase ^= 1; }
  }
};

__device__ __forceinline__ void release_a(uint32_t bars, uint32_t slot, bool next_mc, uint32_t peer, uint32_t cnt) {
  const uint32_t bar = bars + (BAR_AEMPTY + slot) * 8;
  mbar_arrive_n(cnt, bar);
  mbar_arrive_remote_n(next_mc ? cnt : 0u, bar + (BAR_REMPTY - BAR_AEMPTY) * 8, peer);
}

constexpr int OFF_ORD = 480;
__device__ __forceinline__ uint32_t read_order(uint32_t bars, int k) {
  uint32_t v;
  asm volatile(
      "{\n.reg .pred p;\n.reg .b32 n;\nmov.b32 n, 0;\n"
      "WAIT_%=:\n"
      "mbarrier.try_wait.parity.acquire.cluster.shared::cta.b64 p, [%1], 0;\n"
      "@p bra DONE_%=;\n"
      "add.u32 n, n, 1;\n"
      "setp.lt.u32 p, n, %3;\n"
      "@p bra WAIT_%=;\n"
      "trap;\n"
      "DONE_%=:\n"
      "ld.volatile.shared.u32 %0, [%2];\n}\n"
      : "=r"(v) : "r"(bars + (BAR_ORD + k) * 8), "r"(bars + OFF_ORD + k * 4), "n"(SPIN_LIMIT) : "memory");
  return __shfl_sync(0xffffffffu, v, 0);
}

__device__ __forceinline__ void store_block_t(const float (&acc)[80], uint32_t blk, int warp, int lane) {
  const uint32_t addr = blk + ((lane & 7) + ((lane >> 4) << 3)) * 128 + (((2 * warp + ((lane >> 3) & 1)) ^ (lane & 7)) << 4);
#pragma unroll
  for (int j = 0; j < 10; j++) {
    stsm_x4_t(addr + j * 2048, pack_bf16(acc[8 * j], acc[8 * j + 1]), pack_bf16(acc[8 * j + 2], acc[8 * j + 3]),
              pack_bf16(acc[8 * j + 4], acc[8 * j + 5]), pack_bf16(acc[8 * j + 6], acc[8 * j + 7]));
  }
}
__device__ __forceinline__ uint32_t n_addr(uint32_t addr0, int j) { return (addr0 ^ ((j & 1) << 5)) + (j >> 1) * 4096; }
__device__ __forceinline__ void store_block_n(const float (&acc)[80], float scale, uint32_t addr0) {
#pragma unroll
  for (int j = 0; j < 10; j++) {
    stsm_x4(n_addr(addr0, j), pack_bf16(acc[8 * j] * scale, acc[8 * j + 1] * scale),
            pack_bf16(acc[8 * j + 2] * scale, acc[8 * j + 3] * scale),
            pack_bf16(acc[8 * j + 4] * scale, acc[8 * j + 5] * scale),
            pack_bf16(acc[8 * j + 6] * scale, acc[8 * j + 7] * scale));
  }
}

#define PROF(site, stmt) stmt
#define STAMP(idx)
#define TRACE1(i)
#define TRACE(i)

__device__ __forceinline__ void slow_attention(uint8_t* qblk, const __nv_bfloat16* kp, const __nv_bfloat16* vp, int warp, int lane) {
  auto elem = [&](int d, int q) {
    return reinterpret_cast<__nv_bfloat16*>(qblk + (d >> 6) * B_BLK + (q >> 5) * 4096 + (d & 63) * 64 +
                                            ((((q >> 3) & 3) ^ ((d >> 1) & 3)) << 4) + (q & 7) * 2);
  };
  auto unpack = [](uint2 w, float (&f)[4]) {
    f[0] = __uint_as_float(w.x << 16);
    f[1] = __uint_as_float(w.x & 0xffff0000u);
    f[2] = __uint_as_float(w.y << 16);
    f[3] = __uint_as_float(w.y & 0xffff0000u);
  };
#pragma unroll 1
  for (int q0 = 4 * warp; q0 < SQ; q0 += 16) {
    float qv[4][4], o[4][4], m[4], l[4];
#pragma unroll
    for (int i = 0; i < 4; i++) {
      m[i] = -INFINITY;
      l[i] = 0.f;
#pragma unroll
      for (int c = 0; c < 4; c++) {
        qv[i][c] = __bfloat162float(*elem(4 * lane + c, q0 + i));
        o[i][c] = 0.f;
      }
    }
#pragma unroll 2
    for (int k = 0; k < SK; k++) {
      float kf[4], vf[4];
      unpack(*reinterpret_cast<const uint2*>(kp + (size_t)k * DH + lane * 4), kf);
      unpack(*reinterpret_cast<const uint2*>(vp + (size_t)k * DH + lane * 4), vf);
#pragma unroll
      for (int i = 0; i < 4; i++) {
        float s = qv[i][0] * kf[0] + qv[i][1] * kf[1] + qv[i][2] * kf[2] + qv[i][3] * kf[3];
#pragma unroll
        for (int d = 16; d > 0; d >>= 1) s += __shfl_xor_sync(0xffffffffu, s, d);
        const float mn = fmaxf(m[i], s), alpha = exp2f(m[i] - mn), p = exp2f(s - mn);
        m[i] = mn;
        l[i] = l[i] * alpha + p;
#pragma unroll
        for (int c = 0; c < 4; c++) o[i][c] = o[i][c] * alpha + p * vf[c];
      }
    }
#pragma unroll
    for (int i = 0; i < 4; i++)
#pragma unroll
      for (int c = 0; c < 4; c++) *elem(4 * lane + c, q0 + i) = __float2bfloat16(o[i][c] / l[i]);
  }
}

__global__ void __cluster_dims__(2, 1, 1) __launch_bounds__(512, 1)
mha2_kernel(const __grid_constant__ Maps maps, const __grid_constant__ Ptrs ptrs, const __grid_constant__ Plan plan) {
  extern __shared__ uint8_t smem_raw[];
  uint8_t* smem = smem_raw + ((1024 - (smem_u32(smem_raw) & 1023)) & 1023);
  const uint32_t sbase = smem_u32(smem);
  const uint32_t bars = sbase + OFF_BAR;
  const int tid = threadIdx.x, lane = tid & 31;
  const int warp = __shfl_sync(0xffffffffu, (tid >> 5) & 3, 0);
  const uint32_t zero = blockIdx.y;
  const int wg = __shfl_sync(0xffffffffu, tid >> 7, 0);
  const uint32_t rank = blockIdx.x & 1, peer = rank ^ 1;
  uint8_t* const scratch = scratch_base();
  volatile uint32_t* role_slot = reinterpret_cast<volatile uint32_t*>(smem + OFF_BAR + 504);

  uint32_t side = 0;
  if (SIDE_AWARE && (tid >> 5) == 1 && rank == 0) {
#pragma unroll 1
    for (int i = 0; i < PROBE_REP; i++) {
      side = local_selector(scratch, 5, blockIdx.x >> 1, lane);
    }
  }
  if (SIDE_AWARE && tid == 32 && rank == 0) {
    const uint32_t ncl = gridDim.x >> 1, half = ncl >> 1;
    const uint32_t old = atomicAdd(&g_claim, side ? 0x10000u : 1u);
    const uint32_t t = side ? old >> 16 : old & 0xffffu;
    uint32_t role = side * 64 + t;
    if (t >= half) {
      uint32_t v, n = 0;
      while (true) {
        asm volatile("ld.relaxed.gpu.global.u32 %0, [%1];" : "=r"(v) : "l"(&g_claim) : "memory");
        if ((v >> 16) + (v & 0xffffu) >= ncl) break;
        if (++n > (SPIN_LIMIT >> 2)) __trap();
      }
      role = (side ^ 1) * 64 + (side ? v & 0xffffu : v >> 16) + (t - half);
    }
    *role_slot = role;
    asm volatile("fence.release.sync_restrict::shared::cta.cluster;" ::: "memory");
  }
  if (tid >= 64 && tid < 64 + (int)(sizeof(Maps) / sizeof(CUtensorMap)))
    asm volatile("prefetch.tensormap [%0];" ::"l"(reinterpret_cast<const CUtensorMap*>(&maps) + (tid - 64)) : "memory");
  if (tid == 0) {
    for (int i = 0; i < NA; i++) {
      mbar_init(bars + (BAR_AEMPTY + i) * 8, 8);
      mbar_init(bars + (BAR_REMPTY + i) * 8, 8);
    }
    for (int i = 0; i < 4; i++) {
      mbar_init(bars + (BAR_XFULL + i) * 8, 1);
      mbar_init(bars + (BAR_FO + i) * 8, 1);
      mbar_init(bars + (BAR_FO + 4 + i) * 8, 1);
      mbar_init(bars + (BAR_FG + i) * 8, 1);
      mbar_init(bars + (BAR_FS + i) * 8, 1);
      mbar_init(bars + (BAR_XEMPTY + i) * 8, 12);
      mbar_init(bars + (BAR_PFULL + i) * 8, 4);
    }
    for (int i = 0; i < 2; i++) {
      mbar_init(bars + (BAR_QFULL + i) * 8, 8);
      mbar_init(bars + (BAR_QEMPTY + i) * 8, 1);
    }
    mbar_init(bars + BAR_PDONE * 8, 4);
    mbar_init(bars + BAR_BANK * 8, 1);
    mbar_init(bars + BAR_GLAST * 8, 8);
    for (int i = 0; i < DYN; i++) {
      mbar_init(bars + (BAR_ORD + i) * 8, 1);
      mbar_arrive_expect_tx(bars + (BAR_ORD + i) * 8, 4);
    }
    mbar_init(bars + BAR_LREADY * 8, 8);
    mbar_init(bars + BAR_OSTORE * 8, 4);
    asm volatile("fence.mbarrier_init.release.cluster;" ::: "memory");
  }
  __syncthreads();
  cluster_sync();
  uint32_t role;
  asm volatile("{\n.reg .b32 ra;\nmapa.shared::cluster.u32 ra, %1, 0;\nld.volatile.shared::cluster.u32 %0, [ra];\n}\n"
               : "=r"(role) : "r"(bars + 504) : "memory");
  role = SIDE_AWARE ? __shfl_sync(0xffffffffu, role, 0) : ((blockIdx.x >> 1) & 1) * 64 + (blockIdx.x >> 2);
  if (SIDE_AWARE && tid == 480 && rank == 0) {
    if (atomicAdd(&g_claim_done, 1) == (gridDim.x >> 1) - 1) {
      g_claim = 0;
      g_claim_done = 0;
    }
  }
  __syncwarp();
  const int br = role >> 6;
  const uint32_t* const units = plan.unit[role & 63];
  const int cta = (role & 63) < 32 ? (br * 32 + (role & 63)) * 2 + rank : 128 + br * 2 + rank;

  if (wg == 3) {
    asm volatile("setmaxnreg.dec.sync.aligned.u32 32;");
    if (warp < 2 && (units[0] >> 20)) {
      const uint32_t c0 = clock(), d = (units[0] >> 20) * 256;
      while ((uint32_t)clock() - c0 < d) __nanosleep(50);
    }
    if (warp == 0) {
      uint64_t pol;
      asm volatile("createpolicy.fractional.L2::evict_first.b64 %0, 1.0;" : "=l"(pol));
      uint64_t pol_wq = pol, pol_wo = pol;
      if (!WQ_EF) asm volatile("createpolicy.fractional.L2::evict_normal.b64 %0, 1.0;" : "=l"(pol_wq));
      if (!WO_EF) asm volatile("createpolicy.fractional.L2::evict_normal.b64 %0, 1.0;" : "=l"(pol_wo));
      ARing r{0, 1};
      uint32_t rm = 0x3F;
#pragma unroll 1
      for (int u = 0;; u++) {
        const Unit un{units[u]};
        const int ty = un.type();
        if (ty == U_END) break;
        const int arg = un.arg(), b = un.bp() * 2 + rank;
        if (ty == U_AT) {
          const CUtensorMap *mk = &maps.k[br], *mv = &maps.v[br];
          const int row0 = (b * NH + arg) * SK;
          const Unit nx{units[u + 1]};
          const int row_next = ((nx.bp() * 2 + rank) * NH + nx.arg()) * SK - 16 * 64;
#pragma unroll 1
          for (int j = un.prev_at() ? 0 : -2; j < 16; j++) {
            if (j < 14 || un.next_at()) {
              const uint32_t full = bars + (BAR_FS + ((j + 2) & 3)) * 8;
              PROF(0, MW_A(bars + (BAR_AEMPTY + r.slot) * 8, r.phase));
              if (elect_one()) {
                mbar_arrive_expect_tx(full, A_SLOT);
                tma_3d_hint(sbase + r.slot * A_SLOT, mk, (j < 14 ? row0 : row_next) + (j + 2) * 64, full, pol);
              }
              r.adv(1);
            }
            if (j >= 0) {
              const uint32_t full = bars + (BAR_FO + (j & 7)) * 8;
              PROF(0, MW_A(bars + (BAR_AEMPTY + r.slot) * 8, r.phase));
              if (elect_one()) {
                mbar_arrive_expect_tx(full, A_SLOT);
                tma_3d_hint(sbase + r.slot * A_SLOT, mv, row0 + j * 64, full, pol);
              }
              r.adv(1);
            }
          }
        } else {
          const CUtensorMap* mw = ty == U_OP ? &maps.wo[br] : &maps.wq[br];
          const int col = arg * (ty == U_HQ ? 128 : 256) + rank * 64;
          const int n = ty == U_OP ? 64 : 16;
          int row = 0;
          const uint64_t wpol = ty == U_OP ? pol_wo : pol_wq;
#pragma unroll 1
          for (int s = 0; s < n; s++) {
            if (ty == U_OP && (s & 1) == 0) {
              int hi = s >> 1;
              if (hi >= NH - DYN) hi = NH - DYN + (read_order(bars, hi - (NH - DYN)) & 255);
              row = plan.op_head[hi] * DH;
            }
#pragma unroll 1
            for (int i = ty == U_HQ ? 1 : 0; i < 2; i++) {
              const uint32_t full = bars + (i == 0 ? BAR_FO + (s & 7) : ((ty == U_HQ && !(s & 4) == un.keep0()) ? BAR_FS : BAR_FG) + (s & 3)) * 8;
              PROF(0, MW_A(bars + (BAR_AEMPTY + r.slot) * 8, r.phase));
              PROF(1, MW_A(bars + (BAR_REMPTY + r.slot) * 8, (rm >> r.slot) & 1));
              rm ^= 1u << r.slot;
              if (elect_one()) {
                mbar_arrive_expect_tx(full, A_SLOT);
                tma_2d_mc(sbase + r.slot * A_SLOT + rank * 8192, mw, col + (i ^ 1) * 128, row, full, wpol);
              }
              r.adv(1);
            }
            row += 64;
          }
        }
      }
    } else if (warp == 1) {
      uint32_t qm = 0, pdph = 0;
#pragma unroll 1
      for (int u = 0;; u++) {
        const Unit un{units[u]};
        const int ty = un.type();
        if (ty == U_END) break;
        const int b = un.bp() * 2 + rank, bh0 = (br * NB + b) * NH;
        if (ty == U_AT) {
          if (un.qloaded()) {
            const int slot = bh0 + un.arg(), qb = un.qbuf();
            uint32_t sel;
            PROF(2, sel = wait_flag(&g_qflag[slot]));
            const uint32_t full = bars + (BAR_QFULL + qb) * 8;
            MW_B(bars + (BAR_QEMPTY + qb) * 8, ((qm >> qb) & 1) ^ 1);
            MW_B(bars + BAR_XEMPTY * 8, 1);
            MW_B(bars + (BAR_XEMPTY + 1) * 8, 1);
            if (elect_one()) {
              g_qflag[slot] = 0;
              mbar_expect_tx(full, 2 * B_BLK);
              mbar_arrive(full, 8);
              const uint32_t off = slot_off(slot);
#pragma unroll 1
              for (int i = 0; i < 10; i++)
                bulk_g2s(sbase + OFF_B + 2 * qb * B_BLK + i * 4096, scratch + piece_off(off + i * 8192, sel), 4096, full);
            }
            qm ^= 1u << qb;
          }
        } else {
          const int n = ty == U_OP ? 64 : 16, rot = un.rot();
          const bool prev_at = un.prev_at();
          uint32_t off = 0, sel = 0, todo = (1u << DYN) - 1;
#pragma unroll 1
          for (int s = 0; s < n; s++) {
            const int x = x_block(s, rot);
            if (ty == U_OP && (s & 1) == 0) {
              int hi = s >> 1;
              if (hi >= NH - DYN) {
                const int k = hi - (NH - DYN);
                uint32_t msg;
                if (rank == 0) {
                  const int c = lane % (DYN ? DYN : 1), rk = (lane / (DYN ? DYN : 1)) & 1;
                  const uint32_t* f = reinterpret_cast<const uint32_t*>(&g_oflag[bh0 + rk * NH + plan.op_head[NH - DYN + c]]) + un.arg();
                  uint32_t v, ready, cnt = 0;
                  while (true) {
                    asm volatile("ld.acquire.gpu.global.u32 %0, [%1];" : "=r"(v) : "l"(f) : "memory");
                    const uint32_t m = __ballot_sync(0xffffffffu, v != 0);
                    ready = m & (m >> DYN) & todo;
                    if (ready) break;
                    if (++cnt > (SPIN_LIMIT >> 2)) __trap();
                  }
                  const int i = __ffs(ready) - 1;
                  todo &= ~(1u << i);
                  msg = i | (__shfl_sync(0xffffffffu, v, i) << 8) | (__shfl_sync(0xffffffffu, v, i + DYN) << 10);
                  if (lane < 2)
                    asm volatile(
                        "{\n.reg .b32 a, m;\nmapa.shared::cluster.u32 a, %0, %3;\nmapa.shared::cluster.u32 m, %1, %3;\n"
                        "st.async.weak.shared::cluster.mbarrier::complete_tx::bytes.b32 [a], %2, [m];\n}\n" ::"r"(bars + OFF_ORD + k * 4),
                        "r"(bars + (BAR_ORD + k) * 8), "r"(msg), "r"(lane) : "memory");
                } else {
                  msg = read_order(bars, k);
                }
                fence_async_global();
                hi = NH - DYN + (msg & 255);
                sel = (msg >> (8 + 2 * rank)) & 1;
              }
              const int slot = bh0 + plan.op_head[hi];
              off = slot_off(slot);
              uint32_t* f = reinterpret_cast<uint32_t*>(&g_oflag[slot]) + un.arg();
              if ((s >> 1) < NH - DYN) PROF(2, sel = wait_flag(f));
              if (s >= 52) TRACE1(56 + ((s - 52) >> 1));
              if (elect_one()) *f = 0;
            }
            if (s <= 4) {
              if (x == 0) PROF(4, MW_B(bars + (BAR_QEMPTY + 1) * 8, ((qm >> 1) & 1) ^ 1));
              if (s == 2 && prev_at) { MW_B(bars + BAR_PDONE * 8, pdph); pdph ^= 1; }
            }
            const uint32_t full = bars + (BAR_XFULL + x) * 8, dst = sbase + OFF_B + (2 + x) * B_BLK;
            PROF(3, MW_B(bars + (BAR_XEMPTY + x) * 8, x_parity(s, rot) ^ 1));
            if (elect_one()) {
              mbar_arrive_expect_tx(full, B_BLK);
              if (ty != U_OP) {
                tma_2d(dst, &maps.x[br], s * 64, b * SQ, full);
              } else {
#pragma unroll
                for (int i = 0; i < 5; i++)
                  bulk_g2s(dst + i * 4096, scratch + piece_off(off + ((s & 1) * 5 + i) * 8192, sel), 4096, full);
              }
            }
          }
          qm ^= ty == U_HQ ? 1 : 3;
        }
      }
    } else if (warp == 2) {
      uint32_t qm = 0, oph = 0;
      uint32_t known = 0, selmask = 0;
#pragma unroll 1
      for (int i = 0; LOCAL_SCRATCH; i++) {
        const Unit un{units[i >> 1]};
        if (un.type() == U_END) break;
        if (un.type() == U_OP) continue;
        const uint32_t page = ((br * NB + un.bp() * 2 + rank) * NH + (un.type() != U_QP ? un.arg() : 2 * un.arg() + (i & 1))) / SLOTS_PER_PAGE;
        if ((known >> page) & 1) continue;
        uint32_t votes = 0;
#pragma unroll 1
        for (int j = 0; j < 3; j++) votes += local_selector(scratch + page * PAGE, j, cta & 127, lane);
        known |= 1u << page;
        selmask |= (votes >> 1) << page;
      }
      auto store_slot = [&](uint32_t slot, uint32_t src, bool paced) {
        const uint32_t sel = (selmask >> (slot / SLOTS_PER_PAGE)) & 1, off = slot_off(slot);
#pragma unroll 1
        for (int i = 0; i < 10; i++) {
          bulk_s2g(scratch + piece_off(off + i * 8192, sel), src + i * 4096, 4096);
          if (paced) {
            bulk_commit();
            bulk_wait_read<0>();
            if (ST_SLEEP) __nanosleep(ST_SLEEP);
          }
        }
        bulk_commit();
        return 2 + sel;
      };
#pragma unroll 1
      for (int u = 0; lane == 0; u++) {
        const Unit un{units[u]};
        const int ty = un.type();
        if (ty == U_END) break;
        const int b = un.bp() * 2 + rank, bh0 = (br * NB + b) * NH;
        if (ty == U_AT) {
          const int slot = bh0 + un.arg(), qb = un.qbuf();
          if (un.qloaded()) qm ^= 1u << qb;
          MW_C(bars + BAR_OSTORE * 8, oph);
          oph ^= 1;
          TRACE1(52);
          const uint32_t fv = store_slot(slot, sbase + OFF_B + 2 * qb * B_BLK, (ST_PACE & 1) && (un.next_at() || un.mc_next()));
          TRACE1(53);
          bulk_wait_read<0>();
          mbar_arrive(bars + (BAR_QEMPTY + qb) * 8, 1);
          bulk_wait<0>();
          TRACE1(54);
          fence_async_global();
          asm volatile("fence.release.gpu;" ::: "memory");
          TRACE1(55);
          asm volatile("st.relaxed.gpu.global.v4.u32 [%0], {%1, %1, %1, %1};" ::"l"(&g_oflag[slot]), "r"(fv) : "memory");
        } else if (ty != U_OP) {
          const int slot = bh0 + (ty == U_QP ? 2 : 1) * un.arg();
          const int hi = (ty == U_QP && !un.keep1()) ? 1 : 0, lo = un.keep0() ? 1 : 0;
          uint32_t fv = 0;
#pragma unroll 1
          for (int h = hi; h >= lo; h--) {
            MW_C(bars + (BAR_QFULL + h) * 8, (qm >> h) & 1);
            fv |= store_slot(slot + h, sbase + OFF_B + 2 * h * B_BLK, ST_PACE & 2) << (2 * h);
            bulk_wait_read<0>();
            mbar_arrive(bars + (BAR_QEMPTY + h) * 8, 1);
          }
          if (hi >= lo) {
            bulk_wait<0>();
            fence_async_global();
            asm volatile("fence.release.gpu;" ::: "memory");
#pragma unroll 1
            for (int h = lo; h <= hi; h++)
              asm volatile("st.relaxed.gpu.global.u32 [%0], %1;" ::"l"(&g_qflag[slot + h]), "r"((fv >> (2 * h)) & 3) : "memory");
          }
          qm ^= ty == U_QP ? 3 : 1;
        } else {
#pragma unroll 1
          for (int i = 0; i < 4; i++) {
            MW_C(bars + (BAR_QFULL + (i >> 1)) * 8, (qm >> (i >> 1)) & 1);
            if (!(i & 1)) TRACE1(52 + (i >> 1));
            tma_store_2d(&maps.out, br * DM + un.arg() * 256 + i * 64, b * SQ, sbase + OFF_B + i * B_BLK);
          }
          bulk_commit();
          TRACE1(54);
          bulk_wait_read<0>();
          TRACE1(55);
        }
      }
    }
    if (warp == 3 && Unit{units[1]}.bank() && BANK_N > 0) {
      const int line0 = ((Unit{units[1]}.bp() * 2 + rank) * NH + Unit{units[1]}.arg()) * SK * 2;
      const uint32_t bar = bars + BAR_BANK * 8;
      if (elect_one()) mbar_arrive_expect_tx(bar, BANK_N * 4096);
      __nanosleep(BANK_DELAY);
#pragma unroll 1
      for (int i = 0; i < 2 * BANK_N; i++) {
        const int tile = BANK_FIRST + (i >> 1) * (16 - BANK_FIRST) / (BANK_N > 0 ? BANK_N : 1);
        if (elect_one()) tma_2d(sbase + OFF_SINK, (i & 1) ? &maps.vline[br] : &maps.kline[br], 0, line0 + tile * 128, bar);
        __nanosleep(BANK_PACE);
      }
      MW_C(bar, 0);
    }
    __syncwarp();
    if (END_SYNC) cluster_sync();
  } else if (wg == 0) {
    asm volatile("setmaxnreg.inc.sync.aligned.u32 192;");
    ARing r{0, 0};
    uint32_t lph = 0, gph = 0;
    bool opend = false;
    const uint32_t st_off = (16 * warp + (lane & 15)) * 64 + (((lane >> 4) ^ ((lane & 7) >> 1)) << 4);
#pragma unroll 1
    for (int u = 0;; u++) {
      const Unit un{units[u]};
      const int ty = un.type();
      if (ty == U_END) break;
      const bool mc_next = un.mc_next();
      TRACE(u);
      if (ty == U_HQ) {
        r.adv(4);
        if (mc_next) {
          mbar_wait(bars + BAR_GLAST * 8, gph);
          gph ^= 1;
        }
        TRACE(8 + u);
        continue;
      }
      const bool at = ty == U_AT;
      const int n = ty == U_OP ? 64 : 16;
      const int rot = at ? 0 : un.rot();
      float acc0[80], acc1[80];
      if (at && !un.prev_at()) r.adv(3);
      const bool at_end = at && !un.next_at();
      const uint32_t bfull = bars + (at ? BAR_PFULL - 2 : BAR_XFULL) * 8, bempty = bars + (at ? BAR_PEMPTY - 2 : BAR_XEMPTY) * 8;
      uint32_t x = at ? 2 : rot;
      auto mainloop = [&](auto tb) {
        constexpr int TB = decltype(tb)::value;
        constexpr int KB = TB ? 64 : 2;
        PROF(5, mbar_wait(bfull + x * 8, 0));
        PROF(6, mbar_wait(bars + BAR_FO * 8, 0));
        {
          const uint32_t baddr = sbase + OFF_B + (2 + x) * B_BLK;
          const uint64_t da = make_desc(sbase + r.slot * A_SLOT), db = TB ? make_desc_n(baddr) : make_desc(baddr);
          wgmma_fence();
          wgmma_160_init<1, TB>(acc0, da, db);
          wgmma_160_init<1, TB>(acc1, da + 512, db);
#pragma unroll
          for (int kk = 1; kk < 4; kk++) {
            wgmma_160<1, TB>(acc0, da + kk * 128, db + kk * KB);
            wgmma_160<1, TB>(acc1, da + 512 + kk * 128, db + kk * KB);
          }
          wgmma_commit();
        }
        if (TB && opend) {
          fence_async_smem();
          __syncwarp();
          mbar_arrive_n(1, bars + BAR_OSTORE * 8);
        }
#pragma unroll 1
        for (int s = 1; s < n; s++) {
          const uint32_t pslot = r.slot, px = x;
          r.adv((at_end && s >= 14) ? 1 : 2);
          x = at ? 2 + (s & 1) : x_block(s, rot);
          const uint32_t bpar = at ? (s >> 1) & 1 : x_parity(s, rot);
          const uint32_t afull = bars + (BAR_FO + (s & 7)) * 8;
          const bool okb = mbar_test(bfull + x * 8, bpar), oka = mbar_test(afull, (s >> 3) & 1);
          const uint32_t baddr = sbase + OFF_B + (2 + x) * B_BLK;
          const uint64_t da = make_desc(sbase + r.slot * A_SLOT), db = TB ? make_desc_n(baddr) : make_desc(baddr);
          STAMP(128 + (s & 15) * 4);
          PROF(9, wgmma_wait<0>());
          STAMP(128 + (s & 15) * 4 + 1);
          mbar_arrive_n(1, bempty + px * 8);
          release_a(bars, pslot, s + (at ? 3 : 2) < n ? !at : mc_next, peer, 2);
          if (!okb) PROF(7, mbar_wait(bfull + x * 8, bpar));
          if (!oka) PROF(8, mbar_wait(afull, (s >> 3) & 1));
          if (TB ? s == 64 - OP_S_FIRST : (O_LAST && s == 16 - O_LAST && un.next_at())) {
            mbar_wait(bars + BAR_GLAST * 8, gph);
            gph ^= 1;
          }
          STAMP(128 + (s & 15) * 4 + 2);
          wgmma_fence();
#pragma unroll
          for (int kk = 0; kk < 4; kk++) {
            wgmma_160<1, TB>(acc0, da + kk * 128, db + kk * KB);
            wgmma_160<1, TB>(acc1, da + 512 + kk * 128, db + kk * KB);
          }
          wgmma_commit();
        }
      };
      if (ty == U_QP) {
        STAMP(128);
        mainloop(Int<0>{});
        wgmma_wait<0>();
        STAMP(129);
        mbar_arrive_n(1, bempty + x * 8);
        release_a(bars, r.slot, mc_next, peer, 2);
        r.adv(2);
        mbar_wait(bars + BAR_XEMPTY * 8, 1);
        store_block_n(acc0, Q_SCALE, sbase + OFF_B + 2 * B_BLK + st_off);
        mbar_wait(bars + (BAR_XEMPTY + 1) * 8, 1);
        store_block_n(acc1, Q_SCALE, sbase + OFF_B + 3 * B_BLK + st_off);
        fence_async_smem();
        __syncwarp();
        mbar_arrive_n(2, bars + (BAR_QFULL + 1) * 8);
        STAMP(130);
      } else {
        mainloop(Int<1>{});
        if (at) {
          const uint32_t blk = 2 * un.qbuf();
          PROF(10, mbar_wait(bars + BAR_LREADY * 8, lph));
          lph ^= 1;
          float* linv = reinterpret_cast<float*>(smem + OFF_LINV);
          bool bad = false;
          if (lane < 20) {
            const int qp = warp * 20 + lane;
            const float2* lsum = reinterpret_cast<const float2*>(smem + OFF_LSUM) + qp;
            float2 l = lsum[0];
#pragma unroll
            for (int w = 1; w < 8; w++) {
              const float2 v = lsum[w * (SQ / 2)];
              l.x += v.x;
              l.y += v.y;
            }
            bad = !(l.x >= 9.094947e-13f && l.x <= 1.0995116e12f && l.y >= 9.094947e-13f && l.y <= 1.0995116e12f);
            *reinterpret_cast<float2*>(linv + (qp & 3) * 40 + (qp >> 2) * 2) = make_float2(__fdividef(1.f, l.x), __fdividef(1.f, l.y));
          }
          uint32_t anybad;
          asm volatile("{\n.reg .pred p, q;\nsetp.ne.b32 p, %1, 0;\nbar.red.or.pred q, 1, 128, p;\nselp.b32 %0, 1, 0, q;\n}\n"
                       : "=r"(anybad) : "r"((uint32_t)bad) : "memory");
          const float4* lv = reinterpret_cast<const float4*>(linv + (lane & 3) * 40);
          float4 iv[10];
#pragma unroll
          for (int i = 0; i < EP_PRE; i++) iv[i] = lv[i];
          STAMP(128);
          wgmma_wait<0>();
          STAMP(129);
          mbar_arrive_n(1, bempty + x * 8);
          mbar_arrive_n(1, bars + BAR_PDONE * 8);
          release_a(bars, r.slot, mc_next, peer, 2);
          r.adv(at_end ? 1 : 2);
          if (!__any_sync(0xffffffffu, anybad)) {
            const uint32_t addr = sbase + OFF_B + blk * B_BLK + st_off;
#pragma unroll
            for (int j = 0; j < 10; j++) {
              if (j == 1) {
#pragma unroll
                for (int i = EP_PRE; i < EP_PRE + 3; i++) iv[i] = lv[i];
              }
              if (j == 2) {
#pragma unroll
                for (int i = EP_PRE + 3; i < 10; i++) iv[i] = lv[i];
              }
              stsm_x4(n_addr(addr, j), pack_bf16(acc0[8 * j] * iv[j].x, acc0[8 * j + 1] * iv[j].y),
                      pack_bf16(acc0[8 * j + 2] * iv[j].x, acc0[8 * j + 3] * iv[j].y),
                      pack_bf16(acc0[8 * j + 4] * iv[j].z, acc0[8 * j + 5] * iv[j].w),
                      pack_bf16(acc0[8 * j + 6] * iv[j].z, acc0[8 * j + 7] * iv[j].w));
              stsm_x4(n_addr(addr, j) + B_BLK, pack_bf16(acc1[8 * j] * iv[j].x, acc1[8 * j + 1] * iv[j].y),
                      pack_bf16(acc1[8 * j + 2] * iv[j].x, acc1[8 * j + 3] * iv[j].y),
                      pack_bf16(acc1[8 * j + 4] * iv[j].z, acc1[8 * j + 5] * iv[j].w),
                      pack_bf16(acc1[8 * j + 6] * iv[j].z, acc1[8 * j + 7] * iv[j].w));
            }
          } else {
            const size_t off = (size_t)((un.bp() * 2 + rank) * NH + un.arg()) * SK * DH;
            slow_attention(smem + OFF_B + blk * B_BLK, ptrs.k[br] + off, ptrs.v[br] + off, warp, lane);
          }
          opend = DEFER_O && un.next_at();
          if (!opend) {
            fence_async_smem();
            __syncwarp();
            mbar_arrive_n(1, bars + BAR_OSTORE * 8);
          }
          STAMP(130);
        } else {
          wgmma_wait<0>();
          mbar_arrive_n(1, bempty + x * 8);
          mbar_wait(bars + BAR_XEMPTY * 8, 1);
          store_block_t(acc0, sbase + OFF_B + 2 * B_BLK, warp, lane);
          mbar_wait(bars + (BAR_XEMPTY + 1) * 8, 1);
          store_block_t(acc1, sbase + OFF_B + 3 * B_BLK, warp, lane);
          fence_async_smem();
          __syncwarp();
          mbar_arrive_n(2, bars + (BAR_QFULL + 1) * 8);
        }
      }
      TRACE(8 + u);
    }
    if (END_SYNC) cluster_sync();
  } else {
    asm volatile("setmaxnreg.inc.sync.aligned.u32 144;");
    const int si = wg - 1;
    ARing r{0, 0};
    uint32_t qm = 0;
    const uint32_t st_off = (16 * warp + (lane & 15)) * 64 + (((lane >> 4) ^ ((lane & 7) >> 1)) << 4);
#pragma unroll 1
    for (int u = 0;; u++) {
      const Unit un{units[u]};
      const int ty = un.type();
      if (ty == U_END) break;
      const bool mc_next = un.mc_next();
      TRACE(16 + si * 16 + u);
      if (ty == U_AT) {
        const uint32_t qb = un.qbuf();
        if (un.qloaded()) qm ^= 1u << qb;
        PROF(12 + 8 * si, mbar_wait(bars + (BAR_QFULL + qb) * 8, ((qm >> qb) & 1) ^ 1));
        const uint64_t dq = make_desc_n(sbase + OFF_B + 2 * qb * B_BLK);
        const uint32_t paddr = sbase + OFF_B + (4 + si) * B_BLK + st_off;
        uint32_t paddr1 = paddr ^ 32;
        asm volatile("" : "+r"(paddr1));
        float l[40];
#pragma unroll
        for (int i = 0; i < 40; i++) l[i] = 0.f;
        if (!un.prev_at()) r.adv(si);
        bool kok = false;
        if (COLD_STAGGER && si == 1 && !un.prev_at()) {
          const uint32_t c0 = clock();
          while ((uint32_t)clock() - c0 < COLD_STAGGER) {}
        }
        float* lsum = reinterpret_cast<float*>(smem + OFF_LSUM) + (si * 4 + warp) * SQ + (lane & 24) + 2 * (lane & 3) + ((lane >> 2) & 1);
        auto tile = [&](const int t, auto last) {
          constexpr bool LAST = decltype(last)::value;
          float acc[80];
          if (!kok) PROF(13 + 8 * si, mbar_wait(bars + (BAR_FS + si + 2 * (t & 1)) * 8, (t >> 1) & 1));
          STAMP((2 * t + si) * 6);
          const uint64_t dk = make_desc(sbase + r.slot * A_SLOT);
          wgmma_fence();
          wgmma_160_init<0, 1>(acc, dk, dq);
#pragma unroll
          for (int kk = 1; kk < 8; kk++)
            wgmma_160<0, 1>(acc, dk + (kk >> 2) * 512 + (kk & 3) * 2, dq + (kk >> 2) * (B_BLK / 16) + (kk & 3) * 64);
          wgmma_commit();
          if (QK_FIRST) mbar_arrive_n(kok ? 1u : 0u, bars + (BAR_PFULL + si) * 8);
          STAMP((2 * t + si) * 6 + 1);
          PROF(14 + 8 * si, wgmma_wait<0>());
          STAMP((2 * t + si) * 6 + 2);
          release_a(bars, r.slot, LAST ? mc_next : false, peer, 2);
          r.adv((t == 0 && !un.prev_at()) ? 2 + si : ((LAST && !un.next_at()) ? 6 - 2 * si : 4));
          auto expo = [&](int j) {
#pragma unroll
            for (int i = 0; i < 8; i++) acc[8 * j + i] = ex2(acc[8 * j + i]);
          };
          uint32_t pk[40];
          auto sums = [&](int c) {
            float* v = l + 8 * c;
            const bool h4 = lane & 16, h3 = lane & 8, h2 = lane & 4;
#pragma unroll
            for (int i = 0; i < 4; i++) v[i] = (h4 ? v[i + 4] : v[i]) + __shfl_xor_sync(0xffffffffu, h4 ? v[i] : v[i + 4], 16);
#pragma unroll
            for (int i = 0; i < 2; i++) v[i] = (h3 ? v[i + 2] : v[i]) + __shfl_xor_sync(0xffffffffu, h3 ? v[i] : v[i + 2], 8);
            lsum[32 * c] = (h2 ? v[1] : v[0]) + __shfl_xor_sync(0xffffffffu, h2 ? v[0] : v[1], 4);
          };
          auto reduce = [&](int j) {
            l[4 * j] += acc[8 * j] + acc[8 * j + 2];
            l[4 * j + 1] += acc[8 * j + 1] + acc[8 * j + 3];
            l[4 * j + 2] += acc[8 * j + 4] + acc[8 * j + 6];
            l[4 * j + 3] += acc[8 * j + 5] + acc[8 * j + 7];
#pragma unroll
            for (int i = 0; i < 4; i++) pk[4 * j + i] = pack_bf16(acc[8 * j + 2 * i], acc[8 * j + 2 * i + 1]);
            if (LAST && (j & 1) && j < 2 * L_EARLY) sums(j >> 1);
          };
          auto store = [&](int j) { stsm_x4((j & 1 ? paddr1 : paddr) + (j >> 1) * 4096, pk[4 * j], pk[4 * j + 1], pk[4 * j + 2], pk[4 * j + 3]); };
#pragma unroll
          for (int j = 0; j < SM_A; j++) expo(j);
          sched_fence(zero);
#pragma unroll
          for (int j = SM_A; j < SM_B; j++) expo(j);
#pragma unroll
          for (int j = 0; j < SM_A; j++) reduce(j);
          STAMP((2 * t + si) * 6 + 3);
          PROF(15 + 8 * si, mbar_wait(bars + ((t == 0 && !un.prev_at() ? BAR_XEMPTY + 2 : BAR_PEMPTY) + si) * 8, (t & 1) ^ 1));
          STAMP((2 * t + si) * 6 + 4);
#pragma unroll
          for (int j = 0; j < SM_A; j++) store(j);
#pragma unroll
          for (int j = SM_B; j < 10; j++) expo(j);
#pragma unroll
          for (int j = SM_A; j < SM_B; j++) { reduce(j); store(j); }
          if (SM_B < 10) sched_fence(zero);
#pragma unroll
          for (int j = SM_B; j < 10; j++) { reduce(j); store(j); }
          kok = !LAST && mbar_test(bars + (BAR_FS + si + 2 * ((t + 1) & 1)) * 8, ((t + 1) >> 1) & 1);
          fence_async_smem();
          __syncwarp();
          mbar_arrive_n((QK_FIRST && kok) ? 0u : 1u, bars + (BAR_PFULL + si) * 8);
          if (LAST) {
#pragma unroll
            for (int c = L_EARLY; c < 5; c++) sums(c);
            __syncwarp();
            mbar_arrive_n(1, bars + BAR_LREADY * 8);
          }
          STAMP((2 * t + si) * 6 + 5);
        };
#pragma unroll 1
        for (int t = 0; t < 7; t++) tile(t, Int<0>{});
        tile(7, Int<1>{});
      } else {
        float acc[80];
        const int n = ty == U_OP ? 64 : 16;
        const int rot = un.rot();
        const bool hq = ty == U_HQ;
        const uint32_t xcnt = hq ? 2 - si : 1, astep = hq ? 1 : 2;
        r.adv(astep - 1);
        uint32_t x = rot;
        auto mainloop = [&](auto tb) {
          constexpr int TB = decltype(tb)::value;
          constexpr int KB = TB ? 64 : 2;
          STAMP(3 * si);
          mbar_wait(bars + (BAR_XFULL + x) * 8, 0);
          mbar_wait(bars + ((hq && un.keep0()) ? BAR_FS : BAR_FG) * 8, 0);
          {
            const uint32_t baddr = sbase + OFF_B + (2 + x) * B_BLK;
            const uint64_t da = make_desc(sbase + r.slot * A_SLOT + si * 8192), db = TB ? make_desc_n(baddr) : make_desc(baddr);
            wgmma_fence();
            wgmma_160_init<1, TB>(acc, da, db);
#pragma unroll
            for (int kk = 1; kk < 4; kk++) wgmma_160<1, TB>(acc, da + kk * 128, db + kk * KB);
            wgmma_commit();
          }
#pragma unroll 1
          for (int s = 1; s < n; s++) {
            const uint32_t pslot = r.slot, px = x;
            r.adv(astep);
            x = x_block(s, rot);
            const uint32_t bpar = x_parity(s, rot);
            const uint32_t afull = bars + (((hq && !(s & 4) == un.keep0()) ? BAR_FS : BAR_FG) + (s & 3)) * 8, apar = (s >> (hq ? 3 : 2)) & 1;
            const bool okb = mbar_test(bars + (BAR_XFULL + x) * 8, bpar), oka = mbar_test(afull, apar);
            const uint32_t baddr = sbase + OFF_B + (2 + x) * B_BLK;
            const uint64_t da = make_desc(sbase + r.slot * A_SLOT + si * 8192), db = TB ? make_desc_n(baddr) : make_desc(baddr);
            STAMP((s & 15) * 6 + 3 * si);
            PROF(18 + 8 * si, wgmma_wait<0>());
            STAMP((s & 15) * 6 + 3 * si + 1);
            mbar_arrive_n(xcnt, bars + (BAR_XEMPTY + px) * 8);
            release_a(bars, pslot, astep * s - 1 + NA < astep * n ? true : mc_next, peer, 1);
            if (!okb) PROF(16 + 8 * si, mbar_wait(bars + (BAR_XFULL + x) * 8, bpar));
            if (!oka) PROF(17 + 8 * si, mbar_wait(afull, apar));
            STAMP((s & 15) * 6 + 3 * si + 2);
            wgmma_fence();
#pragma unroll
            for (int kk = 0; kk < 4; kk++) wgmma_160<1, TB>(acc, da + kk * 128, db + kk * KB);
            wgmma_commit();
          }
          mbar_arrive_n((TB || (hq ? mc_next : (O_LAST && un.next_at()))) ? 1u : 0u, bars + BAR_GLAST * 8);
          wgmma_wait<0>();
          mbar_arrive_n(xcnt, bars + (BAR_XEMPTY + x) * 8);
          release_a(bars, r.slot, mc_next, peer, 1);
          r.adv(1);
          STAMP(3 * si + 1);
          PROF(19 + 8 * si, mbar_wait(bars + BAR_QEMPTY * 8, (qm & 1) ^ 1));
        };
        if (ty != U_OP) {
          mainloop(Int<0>{});
          store_block_n(acc, Q_SCALE, sbase + OFF_B + si * B_BLK + st_off);
        } else {
          mainloop(Int<1>{});
          store_block_t(acc, sbase + OFF_B + si * B_BLK, warp, lane);
        }
        fence_async_smem();
        __syncwarp();
        mbar_arrive_n(1, bars + BAR_QFULL * 8);
        STAMP(3 * si + 2);
        qm ^= hq ? 1 : 3;
      }
      TRACE(24 + si * 16 + u);
    }
    if (END_SYNC) cluster_sync();
  }
}

typedef CUresult (*EncodeFn)(CUtensorMap*, CUtensorMapDataType, cuuint32_t, void*, const cuuint64_t*, const cuuint64_t*,
                             const cuuint32_t*, const cuuint32_t*, CUtensorMapInterleave, CUtensorMapSwizzle,
                             CUtensorMapL2promotion, CUtensorMapFloatOOBfill);

void make_map_2d(EncodeFn enc, CUtensorMap* m, const void* p, uint64_t cols, uint64_t rows, uint32_t box_rows,
                 CUtensorMapL2promotion promo = W_PROMO) {
  cuuint64_t dims[2] = {cols, rows}, strides[1] = {cols * 2};
  cuuint32_t box[2] = {64, box_rows}, es[2] = {1, 1};
  enc(m, CU_TENSOR_MAP_DATA_TYPE_BFLOAT16, 2, const_cast<void*>(p), dims, strides, box, es, CU_TENSOR_MAP_INTERLEAVE_NONE,
      CU_TENSOR_MAP_SWIZZLE_128B, promo, CU_TENSOR_MAP_FLOAT_OOB_FILL_NONE);
}
void make_map_kv(EncodeFn enc, CUtensorMap* m, const void* p) {
  cuuint64_t dims[3] = {64, (cuuint64_t)NB * NH * SK, 2}, strides[2] = {DH * 2, 128};
  cuuint32_t box[3] = {64, 64, 2}, es[3] = {1, 1, 1};
  enc(m, CU_TENSOR_MAP_DATA_TYPE_BFLOAT16, 3, const_cast<void*>(p), dims, strides, box, es, CU_TENSOR_MAP_INTERLEAVE_NONE,
      CU_TENSOR_MAP_SWIZZLE_128B, KV_PROMO, CU_TENSOR_MAP_FLOAT_OOB_FILL_NONE);
}

void make_map_lines(EncodeFn enc, CUtensorMap* m, const void* p) {
  cuuint64_t dims[2] = {64, (cuuint64_t)NB * NH * SK * 2}, strides[1] = {128};
  cuuint32_t box[2] = {8, 128}, es[2] = {1, 1};
  enc(m, CU_TENSOR_MAP_DATA_TYPE_BFLOAT16, 2, const_cast<void*>(p), dims, strides, box, es, CU_TENSOR_MAP_INTERLEAVE_NONE,
      CU_TENSOR_MAP_SWIZZLE_NONE, CU_TENSOR_MAP_L2_PROMOTION_L2_128B, CU_TENSOR_MAP_FLOAT_OOB_FILL_NONE);
}

void make_plan(Plan* p, bool spare) {
  enum { F_QBUF1 = 1 << 10, F_LOAD = 1 << 11, F_KEEP0 = 1 << 12, F_BANK = 1 << 13, F_KEEP1 = 1 << 17 };
  const char* with_spare[9] = {PLAN_G0, PLAN_A0, PLAN_G1, PLAN_A1, PLAN_G2, PLAN_A2, PLAN_G3, PLAN_A3, "a"};
  const char* without[9] = {"qqQaxo", "haaaaaaa", "qqQaxo", "haaaaaaa", "hbqqqo", "haaaaaaa", "hbqqqo", "haaaaaaa", ""};
  const char* const* prog = spare ? with_spare : without;
  const int delay_spare[9] = {GD0, STAG0, GD1, STAG1, GD2, STAG2, GD3, STAG3, 0}, delay_without[9] = {0, 0, 0, 10, 0, 20, 0, 30, 0};
  const int* delay = spare ? delay_spare : delay_without;
  struct Slot { float t; int a, b; };
  Slot supply[NH], demand[NH];
  int ns = 0, nd = 0, next_pair = 0, next_single = NH - 1;
  int type[9][MAX_UNITS], arg[9][MAX_UNITS], flags[9][MAX_UNITS], len[9];
  float tend[9][MAX_UNITS];
  for (int k = 0; k < MAX_UNITS; k++)
    for (int r = 0; r < 9; r++) {
      if (k == 0) len[r] = (int)strlen(prog[r]);
      if (k >= len[r]) continue;
      const char c = prog[r][k];
      const float t0 = k ? tend[r][k - 1] : (r == 8 ? E_START : delay[r] / 90.f);
      tend[r][k] = t0 + ((c == 'h' || c == 'x') ? 0.6f : 1.f);
      flags[r][k] = k ? 0 : delay[r] << 20;
      if (c == 'q' || c == 'Q' || c == 'K') {
        type[r][k] = U_QP;
        arg[r][k] = next_pair++;
        flags[r][k] |= (c != 'q' ? F_KEEP0 : 0) | (c == 'K' ? F_KEEP1 : 0);
        if (c == 'q') supply[ns++] = {tend[r][k], 2 * arg[r][k], 0};
        if (c != 'K') supply[ns++] = {tend[r][k], 2 * arg[r][k] + 1, 0};
      } else if (c == 'h' || c == 'x') {
        type[r][k] = U_HQ;
        arg[r][k] = next_single--;
        if (c == 'h') flags[r][k] |= F_KEEP0;
        else supply[ns++] = {tend[r][k], arg[r][k], 0};
      } else if (c == 'o') {
        type[r][k] = U_OP;
        arg[r][k] = r >> 1;
      } else {
        type[r][k] = U_AT;
        const char p1 = k > 0 ? prog[r][k - 1] : 0, p2 = k > 1 ? prog[r][k - 2] : 0;
        if (k > 0 && type[r][k - 1] == U_AT && !(flags[r][k - 1] & F_QBUF1)) flags[r][k] |= F_QBUF1;
        if (c == 'b') flags[r][k] |= F_BANK;
        if (p1 == 'h') arg[r][k] = arg[r][k - 1];
        else if (p1 == 'Q' || p1 == 'K') arg[r][k] = 2 * arg[r][k - 1];
        else if (p2 == 'K') arg[r][k] = 2 * arg[r][k - 2] + 1;
        else { flags[r][k] |= F_LOAD; demand[nd++] = {t0, r, k}; }
      }
    }
  auto earlier = [](const Slot& x, const Slot& y) { return x.t < y.t; };
  std::stable_sort(supply, supply + ns, earlier);
  std::stable_sort(demand, demand + nd, earlier);
  for (int i = 0; i < nd; i++) arg[demand[i].a][demand[i].b] = supply[i].a;
  Slot done[NH];
  int ndone = 0;
  for (int role = 0; role < MAX_ROLES; role++) {
    const int r = role == 32 ? 8 : role & 7, n = role == 32 ? 4 * len[8] : len[r];
    for (int k = 0; k < MAX_UNITS; k++) {
      if (k >= n) { p->unit[role][k] = U_END; continue; }
      const int kk = role == 32 ? 0 : k;
      uint32_t d = type[r][kk] | (arg[r][kk] << 3) | ((role == 32 ? k : role >> 3) << 8) | flags[r][kk];
      if (role == 32) d |= ((k & 1) ? F_QBUF1 : 0) | (k == 0 ? E_DELAY << 20 : 0);
      const int prev = k == 0 ? U_END : type[r][role == 32 ? 0 : k - 1], next = k + 1 == n ? U_END : type[r][role == 32 ? 0 : k + 1];
      if (type[r][kk] != U_AT && prev == U_QP) d |= 1u << 14;
      if (prev == U_AT) d |= 1u << 15;
      if (next != U_END) d |= 1u << (next != U_AT ? 16 : 18);
      p->unit[role][k] = d;
      if (type[r][kk] == U_AT && (role < 8 || (role == 32 && k == 3))) done[ndone++] = {tend[r][kk] + (role == 32 ? 3.f : 0.f), arg[r][kk], 0};
    }
  }
  std::stable_sort(done, done + NH, earlier);
  for (int i = 0; i < NH; i++) p->op_head[i] = (uint8_t)done[i].a;
}

}

extern "C" void kernel_launch(void* const* d_in, const int* in_sizes, int n_in, void* d_out, int out_size) {
  (void)in_sizes; (void)n_in; (void)out_size;
  void* fn = nullptr;
  cudaDriverEntryPointQueryResult qr;
  cudaGetDriverEntryPoint("cuTensorMapEncodeTiled", &fn, cudaEnableDefault, &qr);
  EncodeFn enc = reinterpret_cast<EncodeFn>(fn);
  Maps maps;
  Ptrs ptrs;
  for (int br = 0; br < 2; br++) {
    void* const* in = d_in + 5 * br;
    make_map_2d(enc, &maps.x[br], in[0], DM, NB * SQ, SQ, X_PROMO);
    make_map_kv(enc, &maps.k[br], in[1]);
    make_map_kv(enc, &maps.v[br], in[2]);
    make_map_lines(enc, &maps.kline[br], in[1]);
    make_map_lines(enc, &maps.vline[br], in[2]);
    make_map_2d(enc, &maps.wq[br], in[3], NH * DH, DM, 64);
    make_map_2d(enc, &maps.wo[br], in[4], DM, NH * DH, 64);
    ptrs.k[br] = static_cast<const __nv_bfloat16*>(in[1]);
    ptrs.v[br] = static_cast<const __nv_bfloat16*>(in[2]);
  }
  make_map_2d(enc, &maps.out, d_out, 2 * DM, NB * SQ, SQ);
  cudaFuncSetAttribute(mha2_kernel, cudaFuncAttributeMaxDynamicSharedMemorySize, SMEM_BYTES);
  cudaLaunchConfig_t cfg = {};
  cfg.gridDim = 132;
  cfg.blockDim = 512;
  cfg.dynamicSmemBytes = SMEM_BYTES;
  int ncl = 0;
  cudaOccupancyMaxActiveClusters(&ncl, mha2_kernel, &cfg);
  ncl = (USE_E && ncl >= 66) ? 66 : 64;
  Plan plan;
  make_plan(&plan, ncl == 66);
  mha2_kernel<<<2 * ncl, 512, SMEM_BYTES, cudaStreamPerThread>>>(maps, ptrs, plan);
}
```

```cpp
#include <cuda_runtime.h>
#include <cuda_bf16.h>
#include <cuda.h>
#include <stdint.h>
#include <string.h>
#include <algorithm>

namespace {

constexpr int SQ = 160, DM = 1024, NH = 32, SK = 1024, DH = 128, NB = 8;
constexpr int A_SLOT = 16384, NA = 6;
constexpr int B_BLK = 20480;
constexpr int OFF_B = NA * A_SLOT;
constexpr int OFF_LSUM = OFF_B + 6 * B_BLK;
constexpr int OFF_LINV = OFF_LSUM + 8 * SQ * 4;
constexpr int OFF_BAR = OFF_LINV + SQ * 4;
constexpr int OFF_SINK = OFF_BAR + 640 + 1024;
constexpr int SMEM_BYTES = OFF_SINK + 2048 + 1024;
constexpr int BAR_FS = 0;
constexpr int BAR_AEMPTY = 6;
constexpr int BAR_XFULL = 12, BAR_XEMPTY = 16;
constexpr int BAR_PFULL = 20, BAR_PEMPTY = 22;
constexpr int BAR_QFULL = 24, BAR_QEMPTY = 26;
constexpr int BAR_LREADY = 28, BAR_OSTORE = 29, BAR_PDONE = 30;
constexpr int BAR_REMPTY = 31;
constexpr int BAR_FG = 41;
constexpr int BAR_BANK = 45, BAR_GLAST = 46;
constexpr int BAR_FO = 47;
constexpr int BAR_ORD = 55;
constexpr float Q_SCALE = 0.08838834764831845f * 1.4426950408889634f;
constexpr uint32_t SPIN_LIMIT = 1u << 26;
constexpr int DYN = 4;

constexpr int SM_A = 4;
constexpr int SM_B = 7;
constexpr int L_EARLY = 2;
constexpr int EP_PRE = 3;
constexpr int OP_S_FIRST = 2;
constexpr int COLD_STAGGER = 250;
constexpr int BANK_N = 12;
constexpr int BANK_FIRST = 3;
constexpr int BANK_DELAY = 1500;
constexpr int BANK_PACE = 330;

struct Maps {
  CUtensorMap x[2], wq[2], wo[2], k[2], v[2], kline[2], vline[2], out;
};
struct Ptrs {
  uint8_t* scratch;
  const __nv_bfloat16* k[2];
  const __nv_bfloat16* v[2];
};

constexpr int PAGE = 2 << 20, SLOTS_PER_PAGE = 25, SLOT_SPAN = 81920, PROBE_OFF = SLOTS_PER_PAGE * SLOT_SPAN;
constexpr uint32_t PART_MASK = (1u << 13) | (1u << 16) | (1u << 17) | (1u << 19);
__device__ uint4 g_scratch[22 * (PAGE / 16)];

__device__ __forceinline__ uint32_t smem_u32(const void* p) { return (uint32_t)__cvta_generic_to_shared(p); }
__device__ __forceinline__ bool elect_one() {
  uint32_t p;
  asm volatile("{\n.reg .pred p;\nelect.sync _|p, 0xffffffff;\nselp.b32 %0, 1, 0, p;\n}\n" : "=r"(p));
  return p;
}
__device__ __forceinline__ void mbar_init(uint32_t bar, uint32_t cnt) {
  asm volatile("mbarrier.init.shared::cta.b64 [%0], %1;" ::"r"(bar), "r"(cnt));
}
__device__ __forceinline__ void mbar_arrive_expect_tx(uint32_t bar, uint32_t bytes) {
  asm volatile("mbarrier.arrive.expect_tx.shared::cta.b64 _, [%0], %1;" ::"r"(bar), "r"(bytes) : "memory");
}
__device__ __forceinline__ void mbar_expect_tx(uint32_t bar, uint32_t bytes) {
  asm volatile("mbarrier.expect_tx.relaxed.cta.shared::cta.b64 [%0], %1;" ::"r"(bar), "r"(bytes) : "memory");
}
__device__ __forceinline__ void mbar_arrive(uint32_t bar, uint32_t cnt) {
  asm volatile("mbarrier.arrive.shared::cta.b64 _, [%0], %1;" ::"r"(bar), "r"(cnt) : "memory");
}
__device__ __forceinline__ void mbar_arrive_n(uint32_t n, uint32_t bar) {
  asm volatile("{\n.reg .pred p;\n.reg .b32 l;\nmov.u32 l, %%laneid;\nsetp.lt.u32 p, l, %1;\n"
               "@p mbarrier.arrive.shared::cta.b64 _, [%0];\n}\n" ::"r"(bar), "r"(n) : "memory");
}
__device__ __forceinline__ void mbar_arrive_remote_n(uint32_t n, uint32_t bar, uint32_t cta) {
  asm volatile(
      "{\n.reg .pred p;\n.reg .b32 ra, l;\nmov.u32 l, %%laneid;\nsetp.lt.u32 p, l, %2;\nmapa.shared::cluster.u32 ra, %0, %1;\n"
      "@p mbarrier.arrive.shared::cluster.b64 _, [ra];\n}\n" ::"r"(bar), "r"(cta), "r"(n) : "memory");
}
__device__ __forceinline__ void mbar_wait(uint32_t bar, uint32_t parity) {
  asm volatile(
      "{\n.reg .pred p;\n.reg .b32 n;\nmov.b32 n, 0;\n"
      "WAIT_%=:\n"
      "mbarrier.try_wait.parity.shared::cta.b64 p, [%0], %1;\n"
      "@p bra DONE_%=;\n"
      "add.u32 n, n, 1;\n"
      "setp.lt.u32 p, n, %2;\n"
      "@p bra WAIT_%=;\n"
      "trap;\n"
      "DONE_%=:\n}\n" ::"r"(bar), "r"(parity), "n"(SPIN_LIMIT) : "memory");
}
__device__ __forceinline__ void mbar_wait_sleep(uint32_t bar, uint32_t parity) {
  asm volatile(
      "{\n.reg .pred p;\n.reg .b32 n;\nmov.b32 n, 0;\n"
      "WAIT_%=:\n"
      "mbarrier.try_wait.parity.shared::cta.b64 p, [%0], %1, %3;\n"
      "@p bra DONE_%=;\n"
      "add.u32 n, n, 1;\n"
      "setp.lt.u32 p, n, %2;\n"
      "@p bra WAIT_%=;\n"
      "trap;\n"
      "DONE_%=:\n}\n" ::"r"(bar), "r"(parity), "n"(SPIN_LIMIT >> 4), "n"(4000) : "memory");
}
__device__ __forceinline__ bool mbar_test(uint32_t bar, uint32_t parity) {
  uint32_t ok;
  asm volatile("{\n.reg .pred p;\nmbarrier.test_wait.parity.shared::cta.b64 p, [%1], %2;\nselp.b32 %0, 1, 0, p;\n}\n"
               : "=r"(ok) : "r"(bar), "r"(parity) : "memory");
  return ok;
}
__device__ __forceinline__ void tma_2d(uint32_t dst, const CUtensorMap* m, int c0, int c1, uint32_t bar) {
  asm volatile(
      "cp.async.bulk.tensor.2d.shared::cluster.global.mbarrier::complete_tx::bytes [%0], [%1, {%3, %4}], [%2];" ::"r"(dst),
      "l"(m), "r"(bar), "r"(c0), "r"(c1) : "memory");
}
__device__ __forceinline__ void tma_2d_mc(uint32_t dst, const CUtensorMap* m, int c0, int c1, uint32_t bar, uint64_t pol) {
  asm volatile(
      "cp.async.bulk.tensor.2d.shared::cluster.global.mbarrier::complete_tx::bytes.multicast::cluster.L2::cache_hint"
      " [%0], [%1, {%3, %4}], [%2], %5, %6;" ::"r"(dst), "l"(m), "r"(bar), "r"(c0), "r"(c1), "h"((uint16_t)3), "l"(pol) : "memory");
}
__device__ __forceinline__ void tma_3d_hint(uint32_t dst, const CUtensorMap* m, int c1, uint32_t bar, uint64_t pol) {
  asm volatile(
      "cp.async.bulk.tensor.3d.shared::cluster.global.mbarrier::complete_tx::bytes.L2::cache_hint"
      " [%0], [%1, {%4, %3, %4}], [%2], %5;" ::"r"(dst), "l"(m), "r"(bar), "r"(c1), "r"(0), "l"(pol) : "memory");
}
__device__ __forceinline__ void tma_store_2d(const CUtensorMap* m, int c0, int c1, uint32_t src) {
  asm volatile("cp.async.bulk.tensor.2d.global.shared::cta.bulk_group [%0, {%2, %3}], [%1];" ::"l"(m), "r"(src), "r"(c0),
               "r"(c1) : "memory");
}
__device__ __forceinline__ void bulk_g2s(uint32_t dst, const void* src, uint32_t bytes, uint32_t bar) {
  asm volatile("cp.async.bulk.shared::cluster.global.mbarrier::complete_tx::bytes [%0], [%1], %2, [%3];" ::"r"(dst),
               "l"(src), "r"(bytes), "r"(bar) : "memory");
}
__device__ __forceinline__ void bulk_s2g(void* dst, uint32_t src, uint32_t bytes) {
  asm volatile("cp.async.bulk.global.shared::cta.bulk_group [%0], [%1], %2;" ::"l"(dst), "r"(src), "r"(bytes) : "memory");
}
__device__ __forceinline__ void bulk_commit() { asm volatile("cp.async.bulk.commit_group;" ::: "memory"); }
template <int N> __device__ __forceinline__ void bulk_wait_read() { asm volatile("cp.async.bulk.wait_group.read %0;" ::"n"(N) : "memory"); }
template <int N> __device__ __forceinline__ void bulk_wait() { asm volatile("cp.async.bulk.wait_group %0;" ::"n"(N) : "memory"); }
__device__ __forceinline__ void fence_async_smem() { asm volatile("fence.proxy.async.shared::cta;" ::: "memory"); }
__device__ __forceinline__ void fence_async_global() { asm volatile("fence.proxy.async.global;" ::: "memory"); }
__device__ __forceinline__ void wgmma_fence() { asm volatile("wgmma.fence.sync.aligned;" ::: "memory"); }
__device__ __forceinline__ void wgmma_commit() { asm volatile("wgmma.commit_group.sync.aligned;" ::: "memory"); }
template <int N> __device__ __forceinline__ void wgmma_wait() { asm volatile("wgmma.wait_group.sync.aligned %0;" ::"n"(N) : "memory"); }
__device__ __forceinline__ uint64_t make_desc(uint32_t addr) {
  return (uint64_t)((addr & 0x3FFFF) >> 4) | ((uint64_t)1 << 16) | ((uint64_t)64 << 32) | ((uint64_t)1 << 62);
}
__device__ __forceinline__ uint64_t make_desc_n(uint32_t addr) {
  return (uint64_t)((addr & 0x3FFFF) >> 4) | ((uint64_t)256 << 16) | ((uint64_t)32 << 32) | ((uint64_t)2 << 62);
}
__device__ __forceinline__ float ex2(float x) {
  float y;
  asm volatile("ex2.approx.ftz.f32 %0, %1;" : "=f"(y) : "f"(x));
  return y;
}
__device__ __forceinline__ void sched_fence(uint32_t zero) {
  asm volatile("{\n.reg .pred p;\nsetp.eq.b32 p, %0, 0;\nFENCE_%=:\n@p bra.uni FDONE_%=;\nnanosleep.u32 1;\nbra.uni FENCE_%=;\nFDONE_%=:\n}\n" ::"r"(zero) : "memory");
}
__device__ __forceinline__ uint32_t pack_bf16(float lo, float hi) {
  uint32_t r;
  asm("cvt.rn.bf16x2.f32 %0, %1, %2;" : "=r"(r) : "f"(hi), "f"(lo));
  return r;
}
__device__ __forceinline__ void stsm_x4_t(uint32_t addr, uint32_t r0, uint32_t r1, uint32_t r2, uint32_t r3) {
  asm volatile("stmatrix.sync.aligned.m8n8.x4.trans.shared.b16 [%0], {%1, %2, %3, %4};" ::"r"(addr), "r"(r0), "r"(r1),
               "r"(r2), "r"(r3) : "memory");
}
__device__ __forceinline__ void stsm_x4(uint32_t addr, uint32_t r0, uint32_t r1, uint32_t r2, uint32_t r3) {
  asm volatile("stmatrix.sync.aligned.m8n8.x4.shared.b16 [%0], {%1, %2, %3, %4};" ::"r"(addr), "r"(r0), "r"(r1), "r"(r2),
               "r"(r3) : "memory");
}
__device__ __forceinline__ uint32_t wait_flag(const uint32_t* f) {
  uint32_t v, n = 0;
  while (true) {
    asm volatile("ld.acquire.gpu.global.u32 %0, [%1];" : "=r"(v) : "l"(f) : "memory");
    if (v & 4) break;
    if (++n > (SPIN_LIMIT >> 2)) __trap();
    __nanosleep(32);
  }
  fence_async_global();
  return __shfl_sync(0xffffffffu, v, 0);
}

__device__ __forceinline__ uint32_t slot_off(uint32_t slot) {
  return (slot / SLOTS_PER_PAGE) * PAGE + (slot % SLOTS_PER_PAGE) * SLOT_SPAN;
}
__device__ __forceinline__ uint32_t piece_off(uint32_t off, uint32_t sel) {
  return off + (((__popc(off & PART_MASK) ^ sel) & 1) << 12);
}
__device__ __forceinline__ uint32_t local_selector(uint8_t* page, uint32_t pair, uint32_t id, int lane, bool fill) {
  const uint32_t off = PROBE_OFF + pair * 8192;
  uint8_t *p0 = page + piece_off(off, 0) + id * 32, *p1 = page + piece_off(off, 1) + id * 32;
  if (fill && lane < 4) asm volatile("st.global.v4.u32 [%0], {0, 0, 0, 0};" ::"l"((lane & 2 ? p1 : p0) + (lane & 1) * 16) : "memory");
  __syncwarp();
  uint32_t t1 = 0, t2 = 0;
  if (lane == 0)
    asm volatile(
        "{\n.reg .b32 a, b;\n"
        "atom.relaxed.gpu.global.exch.b32 a, [%2], 1;\natom.relaxed.gpu.global.exch.b32 b, [%3], 1;\n"
        "{\n.reg .pred p;\nsetp.eq.u32 p, a, 0xffffffff;\n@p trap;\n}\n"
        "mov.u32 %0, %%clock;\n"
        "{\n.reg .pred p;\nsetp.eq.u32 p, b, 0xffffffff;\n@p trap;\n}\n"
        "mov.u32 %1, %%clock;\n}\n"
        : "=r"(t1), "=r"(t2) : "l"(p0), "l"(p1) : "memory");
  return __shfl_sync(0xffffffffu, t2 - t1 > 100 ? 0u : 1u, 0);
}

template <int TA, int TB>
__device__ __forceinline__ void wgmma_160(float (&d)[80], uint64_t descA, uint64_t descB) {
  asm volatile(
      "wgmma.mma_async.sync.aligned.m64n160k16.f32.bf16.bf16 {"
      "%0, %1, %2, %3, %4, %5, %6, %7, %8, %9, %10, %11, %12, %13, %14, %15, "
      "%16, %17, %18, %19, %20, %21, %22, %23, %24, %25, %26, %27, %28, %29, %30, %31, "
      "%32, %33, %34, %35, %36, %37, %38, %39, %40, %41, %42, %43, %44, %45, %46, %47, "
      "%48, %49, %50, %51, %52, %53, %54, %55, %56, %57, %58, %59, %60, %61, %62, %63, "
      "%64, %65, %66, %67, %68, %69, %70, %71, %72, %73, %74, %75, %76, %77, %78, %79}, "
      "%80, %81, 1, 1, 1, %82, %83;\n"
      : "+f"(d[0]), "+f"(d[1]), "+f"(d[2]), "+f"(d[3]), "+f"(d[4]), "+f"(d[5]), "+f"(d[6]), "+f"(d[7]),
        "+f"(d[8]), "+f"(d[9]), "+f"(d[10]), "+f"(d[11]), "+f"(d[12]), "+f"(d[13]), "+f"(d[14]), "+f"(d[15]),
        "+f"(d[16]), "+f"(d[17]), "+f"(d[18]), "+f"(d[19]), "+f"(d[20]), "+f"(d[21]), "+f"(d[22]), "+f"(d[23]),
        "+f"(d[24]), "+f"(d[25]), "+f"(d[26]), "+f"(d[27]), "+f"(d[28]), "+f"(d[29]), "+f"(d[30]), "+f"(d[31]),
        "+f"(d[32]), "+f"(d[33]), "+f"(d[34]), "+f"(d[35]), "+f"(d[36]), "+f"(d[37]), "+f"(d[38]), "+f"(d[39]),
        "+f"(d[40]), "+f"(d[41]), "+f"(d[42]), "+f"(d[43]), "+f"(d[44]), "+f"(d[45]), "+f"(d[46]), "+f"(d[47]),
        "+f"(d[48]), "+f"(d[49]), "+f"(d[50]), "+f"(d[51]), "+f"(d[52]), "+f"(d[53]), "+f"(d[54]), "+f"(d[55]),
        "+f"(d[56]), "+f"(d[57]), "+f"(d[58]), "+f"(d[59]), "+f"(d[60]), "+f"(d[61]), "+f"(d[62]), "+f"(d[63]),
        "+f"(d[64]), "+f"(d[65]), "+f"(d[66]), "+f"(d[67]), "+f"(d[68]), "+f"(d[69]), "+f"(d[70]), "+f"(d[71]),
        "+f"(d[72]), "+f"(d[73]), "+f"(d[74]), "+f"(d[75]), "+f"(d[76]), "+f"(d[77]), "+f"(d[78]), "+f"(d[79])
      : "l"(descA), "l"(descB), "n"(TA), "n"(TB));
}
template <int TA, int TB>
__device__ __forceinline__ void wgmma_160_init(float (&d)[80], uint64_t descA, uint64_t descB) {
  asm volatile(
      "wgmma.mma_async.sync.aligned.m64n160k16.f32.bf16.bf16 {"
      "%0, %1, %2, %3, %4, %5, %6, %7, %8, %9, %10, %11, %12, %13, %14, %15, "
      "%16, %17, %18, %19, %20, %21, %22, %23, %24, %25, %26, %27, %28, %29, %30, %31, "
      "%32, %33, %34, %35, %36, %37, %38, %39, %40, %41, %42, %43, %44, %45, %46, %47, "
      "%48, %49, %50, %51, %52, %53, %54, %55, %56, %57, %58, %59, %60, %61, %62, %63, "
      "%64, %65, %66, %67, %68, %69, %70, %71, %72, %73, %74, %75, %76, %77, %78, %79}, "
      "%80, %81, 0, 1, 1, %82, %83;\n"
      : "=f"(d[0]), "=f"(d[1]), "=f"(d[2]), "=f"(d[3]), "=f"(d[4]), "=f"(d[5]), "=f"(d[6]), "=f"(d[7]),
        "=f"(d[8]), "=f"(d[9]), "=f"(d[10]), "=f"(d[11]), "=f"(d[12]), "=f"(d[13]), "=f"(d[14]), "=f"(d[15]),
        "=f"(d[16]), "=f"(d[17]), "=f"(d[18]), "=f"(d[19]), "=f"(d[20]), "=f"(d[21]), "=f"(d[22]), "=f"(d[23]),
        "=f"(d[24]), "=f"(d[25]), "=f"(d[26]), "=f"(d[27]), "=f"(d[28]), "=f"(d[29]), "=f"(d[30]), "=f"(d[31]),
        "=f"(d[32]), "=f"(d[33]), "=f"(d[34]), "=f"(d[35]), "=f"(d[36]), "=f"(d[37]), "=f"(d[38]), "=f"(d[39]),
        "=f"(d[40]), "=f"(d[41]), "=f"(d[42]), "=f"(d[43]), "=f"(d[44]), "=f"(d[45]), "=f"(d[46]), "=f"(d[47]),
        "=f"(d[48]), "=f"(d[49]), "=f"(d[50]), "=f"(d[51]), "=f"(d[52]), "=f"(d[53]), "=f"(d[54]), "=f"(d[55]),
        "=f"(d[56]), "=f"(d[57]), "=f"(d[58]), "=f"(d[59]), "=f"(d[60]), "=f"(d[61]), "=f"(d[62]), "=f"(d[63]),
        "=f"(d[64]), "=f"(d[65]), "=f"(d[66]), "=f"(d[67]), "=f"(d[68]), "=f"(d[69]), "=f"(d[70]), "=f"(d[71]),
        "=f"(d[72]), "=f"(d[73]), "=f"(d[74]), "=f"(d[75]), "=f"(d[76]), "=f"(d[77]), "=f"(d[78]), "=f"(d[79])
      : "l"(descA), "l"(descB), "n"(TA), "n"(TB));
}

enum { U_QP = 0, U_AT = 1, U_OP = 2, U_HQ = 3, U_END = 4 };
constexpr int MAX_UNITS = 9, MAX_ROLES = 33;
struct Plan {
  uint32_t unit[MAX_ROLES][MAX_UNITS];
  uint8_t op_head[NH];
};
struct Unit {
  uint32_t d;
  __device__ __forceinline__ int type() const { return d & 7; }
  __device__ __forceinline__ int arg() const { return (d >> 3) & 31; }
  __device__ __forceinline__ int bp() const { return (d >> 8) & 3; }
  __device__ __forceinline__ int qbuf() const { return (d >> 10) & 1; }
  __device__ __forceinline__ bool qloaded() const { return (d >> 11) & 1; }
  __device__ __forceinline__ bool keep0() const { return (d >> 12) & 1; }
  __device__ __forceinline__ bool keep1() const { return (d >> 17) & 1; }
  __device__ __forceinline__ bool bank() const { return (d >> 13) & 1; }
  __device__ __forceinline__ int rot() const { return (d >> 13) & 2; }
  __device__ __forceinline__ bool prev_at() const { return (d >> 15) & 1; }
  __device__ __forceinline__ uint32_t delay() const { return (d >> 20) * 256; }
  __device__ __forceinline__ bool next_at() const { return (d >> 18) & 1; }
  __device__ __forceinline__ bool mc_next() const { return (d >> 16) & 1; }
};

__device__ __forceinline__ uint32_t x_block(int s, int rot) {
  return (rot && s < 16) ? (0x44e4e4eeu >> (2 * s)) & 3 : (s + rot) & 3;
}
__device__ __forceinline__ uint32_t x_parity(int s, int rot) {
  return (rot && s < 16) ? (0xcf0cu >> s) & 1 : (s >> 2) & 1;
}

template <int V> struct Int { static constexpr int value = V; };

struct ARing {
  uint32_t slot, phase;
  __device__ __forceinline__ void adv(uint32_t n) {
    slot += n;
    if (slot >= NA) { slot -= NA; phase ^= 1; }
  }
};

__device__ __forceinline__ void release_a(uint32_t bars, uint32_t slot, bool next_mc, uint32_t peer, uint32_t cnt) {
  const uint32_t bar = bars + (BAR_AEMPTY + slot) * 8;
  mbar_arrive_n(cnt, bar);
  mbar_arrive_remote_n(next_mc ? cnt : 0u, bar + (BAR_REMPTY - BAR_AEMPTY) * 8, peer);
}

constexpr int OFF_ORD = 480;
__device__ __forceinline__ void send_both(uint32_t bars, int k, uint32_t msg, int lane) {
  if (lane < 2)
    asm volatile(
        "{\n.reg .b32 a, m;\nmapa.shared::cluster.u32 a, %0, %3;\nmapa.shared::cluster.u32 m, %1, %3;\n"
        "st.async.weak.shared::cluster.mbarrier::complete_tx::bytes.b32 [a], %2, [m];\n}\n" ::"r"(bars + OFF_ORD + k * 4),
        "r"(bars + (BAR_ORD + k) * 8), "r"(msg), "r"(lane) : "memory");
  __syncwarp();
}
__device__ __forceinline__ uint32_t read_order(uint32_t bars, int k) {
  uint32_t v;
  asm volatile(
      "{\n.reg .pred p;\n.reg .b32 n;\nmov.b32 n, 0;\n"
      "WAIT_%=:\n"
      "mbarrier.try_wait.parity.acquire.cluster.shared::cta.b64 p, [%1], 0;\n"
      "@p bra DONE_%=;\n"
      "add.u32 n, n, 1;\n"
      "setp.lt.u32 p, n, %3;\n"
      "@p bra WAIT_%=;\n"
      "trap;\n"
      "DONE_%=:\n"
      "ld.volatile.shared.u32 %0, [%2];\n}\n"
      : "=r"(v) : "r"(bars + (BAR_ORD + k) * 8), "r"(bars + OFF_ORD + k * 4), "n"(SPIN_LIMIT) : "memory");
  return __shfl_sync(0xffffffffu, v, 0);
}

__device__ __forceinline__ void store_block_t(const float (&acc)[80], uint32_t blk, int warp, int lane) {
  const uint32_t addr = blk + ((lane & 7) + ((lane >> 4) << 3)) * 128 + (((2 * warp + ((lane >> 3) & 1)) ^ (lane & 7)) << 4);
#pragma unroll
  for (int j = 0; j < 10; j++) {
    stsm_x4_t(addr + j * 2048, pack_bf16(acc[8 * j], acc[8 * j + 1]), pack_bf16(acc[8 * j + 2], acc[8 * j + 3]),
              pack_bf16(acc[8 * j + 4], acc[8 * j + 5]), pack_bf16(acc[8 * j + 6], acc[8 * j + 7]));
  }
}
__device__ __forceinline__ uint32_t n_addr(uint32_t addr0, int j) { return (addr0 ^ ((j & 1) << 5)) + (j >> 1) * 4096; }
__device__ __forceinline__ void store_block_n(const float (&acc)[80], float scale, uint32_t addr0) {
#pragma unroll
  for (int j = 0; j < 10; j++) {
    stsm_x4(n_addr(addr0, j), pack_bf16(acc[8 * j] * scale, acc[8 * j + 1] * scale),
            pack_bf16(acc[8 * j + 2] * scale, acc[8 * j + 3] * scale),
            pack_bf16(acc[8 * j + 4] * scale, acc[8 * j + 5] * scale),
            pack_bf16(acc[8 * j + 6] * scale, acc[8 * j + 7] * scale));
  }
}

__device__ __forceinline__ void slow_attention(uint8_t* qblk, const __nv_bfloat16* kp, const __nv_bfloat16* vp, int warp, int lane) {
  auto elem = [&](int d, int q) {
    return reinterpret_cast<__nv_bfloat16*>(qblk + (d >> 6) * B_BLK + (q >> 5) * 4096 + (d & 63) * 64 +
                                            ((((q >> 3) & 3) ^ ((d >> 1) & 3)) << 4) + (q & 7) * 2);
  };
  auto unpack = [](uint2 w, float (&f)[4]) {
    f[0] = __uint_as_float(w.x << 16);
    f[1] = __uint_as_float(w.x & 0xffff0000u);
    f[2] = __uint_as_float(w.y << 16);
    f[3] = __uint_as_float(w.y & 0xffff0000u);
  };
#pragma unroll 1
  for (int q0 = 4 * warp; q0 < SQ; q0 += 16) {
    float qv[4][4], o[4][4], m[4], l[4];
#pragma unroll
    for (int i = 0; i < 4; i++) {
      m[i] = -INFINITY;
      l[i] = 0.f;
#pragma unroll
      for (int c = 0; c < 4; c++) {
        qv[i][c] = __bfloat162float(*elem(4 * lane + c, q0 + i));
        o[i][c] = 0.f;
      }
    }
#pragma unroll 2
    for (int k = 0; k < SK; k++) {
      float kf[4], vf[4];
      unpack(*reinterpret_cast<const uint2*>(kp + (size_t)k * DH + lane * 4), kf);
      unpack(*reinterpret_cast<const uint2*>(vp + (size_t)k * DH + lane * 4), vf);
#pragma unroll
      for (int i = 0; i < 4; i++) {
        float s = qv[i][0] * kf[0] + qv[i][1] * kf[1] + qv[i][2] * kf[2] + qv[i][3] * kf[3];
#pragma unroll
        for (int d = 16; d > 0; d >>= 1) s += __shfl_xor_sync(0xffffffffu, s, d);
        const float mn = fmaxf(m[i], s), alpha = exp2f(m[i] - mn), p = exp2f(s - mn);
        m[i] = mn;
        l[i] = l[i] * alpha + p;
#pragma unroll
        for (int c = 0; c < 4; c++) o[i][c] = o[i][c] * alpha + p * vf[c];
      }
    }
#pragma unroll
    for (int i = 0; i < 4; i++)
#pragma unroll
      for (int c = 0; c < 4; c++) *elem(4 * lane + c, q0 + i) = __float2bfloat16(o[i][c] / l[i]);
  }
}

__global__ void __cluster_dims__(2, 1, 1) __launch_bounds__(512, 1)
mha2_kernel(const __grid_constant__ Ptrs ptrs, const __grid_constant__ Plan plan, const __grid_constant__ Maps maps) {
  extern __shared__ uint8_t smem_raw[];
  uint8_t* smem = smem_raw + ((1024 - (smem_u32(smem_raw) & 1023)) & 1023);
  const uint32_t sbase = smem_u32(smem);
  const uint32_t bars = sbase + OFF_BAR;
  const int tid = threadIdx.x, lane = tid & 31;
  const int warp = __shfl_sync(0xffffffffu, (tid >> 5) & 3, 0);
  const uint32_t zero = blockIdx.y;
  const int wg = __shfl_sync(0xffffffffu, tid >> 7, 0);
  const uint32_t rank = blockIdx.x & 1, peer = rank ^ 1;
  uint8_t* const scratch = ptrs.scratch;
  uint32_t* const taken0 = reinterpret_cast<uint32_t*>(scratch + piece_off(PROBE_OFF + 2 * 8192, 0));
  uint32_t* const taken1 = reinterpret_cast<uint32_t*>(scratch + piece_off(PROBE_OFF + 2 * 8192, 1));
  uint32_t role = 0;
  const bool claimer = wg == 3 && warp == 3 && rank == 0;
  if (claimer) {
    asm volatile("barrier.cluster.arrive.relaxed;" ::: "memory");
    local_selector(scratch, 5, blockIdx.x >> 1, lane, true);
    const uint32_t side = local_selector(scratch, 5, blockIdx.x >> 1, lane, false);
    if (lane == 0) {
      const uint32_t ncl = gridDim.x >> 1, half = ncl >> 1;
      const uint32_t t = atomicAdd(side ? taken1 : taken0, 1u);
      role = side * 64 + t;
      if (t >= half) {
        uint32_t v0, v1, n = 0;
        while (true) {
          asm volatile("ld.relaxed.gpu.global.u32 %0, [%1];" : "=r"(v0) : "l"(taken0) : "memory");
          asm volatile("ld.relaxed.gpu.global.u32 %0, [%1];" : "=r"(v1) : "l"(taken1) : "memory");
          if (v0 + v1 >= ncl) break;
          if (++n > (SPIN_LIMIT >> 2)) __trap();
        }
        role = (side ^ 1) * 64 + (side ? v0 : v1) + (t - half);
      }
    }
    role = __shfl_sync(0xffffffffu, role, 0);
  }
  if (tid >= 64 && tid < 64 + (int)(sizeof(Maps) / sizeof(CUtensorMap)))
    asm volatile("prefetch.tensormap [%0];" ::"l"(reinterpret_cast<const CUtensorMap*>(&maps) + (tid - 64)) : "memory");
  if (tid == 0) {
    for (int i = 0; i < NA; i++) {
      mbar_init(bars + (BAR_AEMPTY + i) * 8, 8);
      mbar_init(bars + (BAR_REMPTY + i) * 8, 8);
    }
    for (int i = 0; i < 4; i++) {
      mbar_init(bars + (BAR_XFULL + i) * 8, 1);
      mbar_init(bars + (BAR_FO + i) * 8, 1);
      mbar_init(bars + (BAR_FO + 4 + i) * 8, 1);
      mbar_init(bars + (BAR_FG + i) * 8, 1);
      mbar_init(bars + (BAR_FS + i) * 8, 1);
      mbar_init(bars + (BAR_XEMPTY + i) * 8, 12);
      mbar_init(bars + (BAR_PFULL + i) * 8, 4);
    }
    for (int i = 0; i < 2; i++) {
      mbar_init(bars + (BAR_QFULL + i) * 8, 8);
      mbar_init(bars + (BAR_QEMPTY + i) * 8, 1);
    }
    mbar_init(bars + BAR_PDONE * 8, 4);
    mbar_init(bars + BAR_BANK * 8, 1);
    mbar_init(bars + BAR_GLAST * 8, 8);
    for (int i = 0; i <= DYN; i++) {
      mbar_init(bars + (BAR_ORD + i) * 8, 1);
      mbar_arrive_expect_tx(bars + (BAR_ORD + i) * 8, 4);
    }
    mbar_init(bars + BAR_LREADY * 8, 8);
    mbar_init(bars + BAR_OSTORE * 8, 4);
    asm volatile("fence.mbarrier_init.release.cluster;" ::: "memory");
  }
  if (!claimer) asm volatile("barrier.cluster.arrive.relaxed;" ::: "memory");
  asm volatile("barrier.cluster.wait;" ::: "memory");
  if (claimer) send_both(bars, DYN, role, lane);
  role = read_order(bars, DYN);
  const int br = role >> 6;
  const uint32_t* const units = plan.unit[role & 63];
  uint32_t* const qflag = reinterpret_cast<uint32_t*>(scratch + piece_off(PROBE_OFF + 3 * 8192, br)) - br * NB * NH;
  uint4* const oflag = reinterpret_cast<uint4*>(scratch + piece_off(PROBE_OFF + 4 * 8192, br)) - br * NB * NH;
  const int cta = (role & 63) < 32 ? (br * 32 + (role & 63)) * 2 + rank : 128 + br * 2 + rank;

  if (wg == 3) {
    asm volatile("setmaxnreg.dec.sync.aligned.u32 32;");
    auto pause = [](uint32_t cycles) {
      const uint32_t c0 = clock();
      while ((uint32_t)clock() - c0 < cycles) __nanosleep(50);
    };
    if (warp < 2) pause(Unit{units[0]}.delay());
    if (warp == 0) {
      uint64_t pol;
      asm volatile("createpolicy.fractional.L2::evict_first.b64 %0, 1.0;" : "=l"(pol));
      uint64_t pol_normal;
      asm volatile("createpolicy.fractional.L2::evict_normal.b64 %0, 1.0;" : "=l"(pol_normal));
      ARing r{0, 1};
      uint32_t rm = 0x3F;
#pragma unroll 1
      for (int u = 0;; u++) {
        const Unit un{units[u]};
        const int ty = un.type();
        if (ty == U_END) break;
        const int arg = un.arg(), b = un.bp() * 2 + rank;
        if (ty == U_AT) {
          const CUtensorMap *mk = &maps.k[br], *mv = &maps.v[br];
          const int row0 = (b * NH + arg) * SK;
          const Unit nx{units[u + 1]};
          const int row_next = ((nx.bp() * 2 + rank) * NH + nx.arg()) * SK - 16 * 64;
#pragma unroll 1
          for (int j = un.prev_at() ? 0 : -2; j < 16; j++) {
            if (j < 14 || un.next_at()) {
              const uint32_t full = bars + (BAR_FS + ((j + 2) & 3)) * 8;
              mbar_wait(bars + (BAR_AEMPTY + r.slot) * 8, r.phase);
              if (elect_one()) {
                mbar_arrive_expect_tx(full, A_SLOT);
                tma_3d_hint(sbase + r.slot * A_SLOT, mk, (j < 14 ? row0 : row_next) + (j + 2) * 64, full, pol);
              }
              r.adv(1);
            }
            if (j >= 0) {
              const uint32_t full = bars + (BAR_FO + (j & 7)) * 8;
              mbar_wait(bars + (BAR_AEMPTY + r.slot) * 8, r.phase);
              if (elect_one()) {
                mbar_arrive_expect_tx(full, A_SLOT);
                tma_3d_hint(sbase + r.slot * A_SLOT, mv, row0 + j * 64, full, pol);
              }
              r.adv(1);
            }
          }
        } else {
          const CUtensorMap* mw = ty == U_OP ? &maps.wo[br] : &maps.wq[br];
          const int col = arg * (ty == U_HQ ? 128 : 256) + rank * 64;
          const int n = ty == U_OP ? 64 : 16;
          int row = 0;
          const uint64_t wpol = ty == U_OP ? pol_normal : pol;
#pragma unroll 1
          for (int s = 0; s < n; s++) {
            if (ty == U_OP && (s & 1) == 0) {
              int hi = s >> 1;
              if (hi >= NH - DYN) hi = NH - DYN + (read_order(bars, hi - (NH - DYN)) & 255);
              row = plan.op_head[hi] * DH;
            }
#pragma unroll 1
            for (int i = ty == U_HQ ? 1 : 0; i < 2; i++) {
              const uint32_t full = bars + (i == 0 ? BAR_FO + (s & 7) : ((ty == U_HQ && !(s & 4) == un.keep0()) ? BAR_FS : BAR_FG) + (s & 3)) * 8;
              mbar_wait(bars + (BAR_AEMPTY + r.slot) * 8, r.phase);
              mbar_wait(bars + (BAR_REMPTY + r.slot) * 8, (rm >> r.slot) & 1);
              rm ^= 1u << r.slot;
              if (elect_one()) {
                mbar_arrive_expect_tx(full, A_SLOT);
                tma_2d_mc(sbase + r.slot * A_SLOT + rank * 8192, mw, col + (i ^ 1) * 128, row, full, wpol);
              }
              r.adv(1);
            }
            row += 64;
          }
        }
      }
    } else if (warp == 1) {
      uint32_t qm = 0, pdph = 0;
#pragma unroll 1
      for (int u = 0;; u++) {
        const Unit un{units[u]};
        const int ty = un.type();
        if (ty == U_END) break;
        const int b = un.bp() * 2 + rank, bh0 = (br * NB + b) * NH;
        if (ty == U_AT) {
          if (un.qloaded()) {
            const int slot = bh0 + un.arg(), qb = un.qbuf();
            const uint32_t sel = wait_flag(&qflag[slot]);
            const uint32_t full = bars + (BAR_QFULL + qb) * 8;
            mbar_wait_sleep(bars + (BAR_QEMPTY + qb) * 8, ((qm >> qb) & 1) ^ 1);
            mbar_wait_sleep(bars + BAR_XEMPTY * 8, 1);
            mbar_wait_sleep(bars + (BAR_XEMPTY + 1) * 8, 1);
            if (elect_one()) {
              qflag[slot] = 0;
              mbar_expect_tx(full, 2 * B_BLK);
              mbar_arrive(full, 8);
              const uint32_t off = slot_off(slot);
#pragma unroll 1
              for (int i = 0; i < 10; i++)
                bulk_g2s(sbase + OFF_B + 2 * qb * B_BLK + i * 4096, scratch + piece_off(off + i * 8192, sel), 4096, full);
            }
            qm ^= 1u << qb;
          }
        } else {
          if (ty == U_OP) pause(un.delay());
          const int n = ty == U_OP ? 64 : 16, rot = un.rot();
          const bool prev_at = un.prev_at();
          uint32_t off = 0, sel = 0, todo = (1u << DYN) - 1;
          uint32_t* flag = nullptr;
#pragma unroll 1
          for (int s = 0; s < n; s++) {
            const int x = x_block(s, rot);
            if (ty == U_OP && (s & 1) == 0) {
              int hi = s >> 1;
              if (hi >= NH - DYN) {
                const int k = hi - (NH - DYN);
                uint32_t msg;
                if (rank == 0) {
                  const int c = lane % DYN, rk = (lane / DYN) & 1;
                  const uint32_t* f = reinterpret_cast<const uint32_t*>(&oflag[bh0 + rk * NH + plan.op_head[NH - DYN + c]]) + un.arg();
                  uint32_t v, ready, cnt = 0;
                  while (true) {
                    asm volatile("ld.acquire.gpu.global.u32 %0, [%1];" : "=r"(v) : "l"(f) : "memory");
                    const uint32_t m = __ballot_sync(0xffffffffu, v != 0);
                    ready = m & (m >> DYN) & todo;
                    if (ready) break;
                    if (++cnt > (SPIN_LIMIT >> 2)) __trap();
                  }
                  const int i = __ffs(ready) - 1;
                  todo &= ~(1u << i);
                  msg = i | (__shfl_sync(0xffffffffu, v, i) << 8) | (__shfl_sync(0xffffffffu, v, i + DYN) << 12);
                  send_both(bars, k, msg, lane);
                } else {
                  msg = read_order(bars, k);
                }
                fence_async_global();
                hi = NH - DYN + (msg & 255);
                sel = (msg >> (8 + 4 * rank)) & 7;
              }
              const int slot = bh0 + plan.op_head[hi];
              off = slot_off(slot);
              flag = reinterpret_cast<uint32_t*>(&oflag[slot]) + un.arg();
              if ((s >> 1) < NH - DYN) sel = wait_flag(flag);
            } else if (ty == U_OP) {
              if (!(sel & 4)) wait_flag(flag);
              if (elect_one()) *flag = 0;
            }
            if (s <= 4) {
              if (x == 0) mbar_wait_sleep(bars + (BAR_QEMPTY + 1) * 8, ((qm >> 1) & 1) ^ 1);
              if (s == 2 && prev_at) { mbar_wait_sleep(bars + BAR_PDONE * 8, pdph); pdph ^= 1; }
            }
            const uint32_t full = bars + (BAR_XFULL + x) * 8, dst = sbase + OFF_B + (2 + x) * B_BLK;
            mbar_wait_sleep(bars + (BAR_XEMPTY + x) * 8, x_parity(s, rot) ^ 1);
            if (elect_one()) {
              mbar_arrive_expect_tx(full, B_BLK);
              if (ty != U_OP) {
                tma_2d(dst, &maps.x[br], s * 64, b * SQ, full);
              } else {
#pragma unroll
                for (int i = 0; i < 5; i++)
                  bulk_g2s(dst + i * 4096, scratch + piece_off(off + ((s & 1) * 5 + i) * 8192, sel), 4096, full);
              }
            }
          }
          qm ^= ty == U_HQ ? 1 : 3;
        }
      }
    } else if (warp == 2) {
      uint32_t qm = 0, oph = 0;
      uint32_t known = 0, selmask = 0;
#pragma unroll 1
      for (int i = 0;; i++) {
        const Unit un{units[i >> 1]};
        if (un.type() == U_END) break;
        if (un.type() == U_OP) continue;
        const uint32_t page = ((br * NB + un.bp() * 2 + rank) * NH + (un.type() != U_QP ? un.arg() : 2 * un.arg() + (i & 1))) / SLOTS_PER_PAGE;
        if ((known >> page) & 1) continue;
        uint32_t votes = 0;
#pragma unroll 1
        for (int j = 0; j < 4; j++) {
          const uint32_t v = local_selector(scratch + page * PAGE, cta >> 7, cta & 127, lane, j == 0);
          if (j) votes += v;
        }
        known |= 1u << page;
        selmask |= (votes >> 1) << page;
      }
      auto store_slot = [&](uint32_t slot, uint32_t src, bool urgent) {
        const uint32_t sel = (selmask >> (slot / SLOTS_PER_PAGE)) & 1, off = slot_off(slot);
#pragma unroll 1
        for (int i = 0; i < 10; i++) {
          bulk_s2g(scratch + piece_off(off + i * 8192, sel), src + i * 4096, 4096);
          if (i == 4 && urgent) {
            bulk_commit();
            bulk_wait<0>();
            fence_async_global();
            asm volatile("fence.release.gpu;" ::: "memory");
            asm volatile("st.relaxed.gpu.global.v4.u32 [%0], {%1, %1, %1, %1};" ::"l"(&oflag[slot]), "r"(2 + sel) : "memory");
          }
        }
        bulk_commit();
        return 6 + sel;
      };
#pragma unroll 1
      for (int u = 0; lane == 0; u++) {
        const Unit un{units[u]};
        const int ty = un.type();
        if (ty == U_END) break;
        const int b = un.bp() * 2 + rank, bh0 = (br * NB + b) * NH;
        if (ty == U_AT) {
          const int slot = bh0 + un.arg(), qb = un.qbuf();
          if (un.qloaded()) qm ^= 1u << qb;
          mbar_wait_sleep(bars + BAR_OSTORE * 8, oph);
          oph ^= 1;
          const uint32_t fv = store_slot(slot, sbase + OFF_B + 2 * qb * B_BLK, !un.next_at() && !un.mc_next());
          bulk_wait_read<0>();
          mbar_arrive(bars + (BAR_QEMPTY + qb) * 8, 1);
          bulk_wait<0>();
          fence_async_global();
          asm volatile("fence.release.gpu;" ::: "memory");
          asm volatile("st.relaxed.gpu.global.v4.u32 [%0], {%1, %1, %1, %1};" ::"l"(&oflag[slot]), "r"(fv) : "memory");
        } else if (ty != U_OP) {
          const int slot = bh0 + (ty == U_QP ? 2 : 1) * un.arg();
          const int hi = (ty == U_QP && !un.keep1()) ? 1 : 0, lo = un.keep0() ? 1 : 0;
          uint32_t fv = 0;
#pragma unroll 1
          for (int h = hi; h >= lo; h--) {
            mbar_wait_sleep(bars + (BAR_QFULL + h) * 8, (qm >> h) & 1);
            fv |= store_slot(slot + h, sbase + OFF_B + 2 * h * B_BLK, false) << (4 * h);
            bulk_wait_read<0>();
            mbar_arrive(bars + (BAR_QEMPTY + h) * 8, 1);
          }
          if (hi >= lo) {
            bulk_wait<0>();
            fence_async_global();
            asm volatile("fence.release.gpu;" ::: "memory");
#pragma unroll 1
            for (int h = lo; h <= hi; h++)
              asm volatile("st.relaxed.gpu.global.u32 [%0], %1;" ::"l"(&qflag[slot + h]), "r"((fv >> (4 * h)) & 7) : "memory");
          }
          qm ^= ty == U_QP ? 3 : 1;
        } else {
#pragma unroll 1
          for (int i = 0; i < 4; i++) {
            mbar_wait_sleep(bars + (BAR_QFULL + (i >> 1)) * 8, (qm >> (i >> 1)) & 1);
            tma_store_2d(&maps.out, br * DM + un.arg() * 256 + i * 64, b * SQ, sbase + OFF_B + i * B_BLK);
          }
          bulk_commit();
          bulk_wait_read<0>();
        }
      }
    }
    if (claimer && lane == 0) {
      if (atomicAdd(taken0 + 1, 1) == (gridDim.x >> 1) - 1) {
        taken0[0] = 0;
        taken0[1] = 0;
        taken1[0] = 0;
      }
    }
    __syncwarp();
    if (warp == 3 && Unit{units[1]}.bank()) {
      const int line0 = ((Unit{units[1]}.bp() * 2 + rank) * NH + Unit{units[1]}.arg()) * SK * 2;
      const uint32_t bar = bars + BAR_BANK * 8;
      if (elect_one()) mbar_arrive_expect_tx(bar, BANK_N * 4096);
      __nanosleep(BANK_DELAY);
#pragma unroll 1
      for (int i = 0; i < 2 * BANK_N; i++) {
        const int tile = BANK_FIRST + (i >> 1) * (16 - BANK_FIRST) / BANK_N;
        if (elect_one()) tma_2d(sbase + OFF_SINK, (i & 1) ? &maps.vline[br] : &maps.kline[br], 0, line0 + tile * 128, bar);
        __nanosleep(BANK_PACE);
      }
      mbar_wait_sleep(bar, 0);
    }
    __syncwarp();
  } else if (wg == 0) {
    asm volatile("setmaxnreg.inc.sync.aligned.u32 192;");
    ARing r{0, 0};
    uint32_t lph = 0, gph = 0;
    bool opend = false;
    const uint32_t st_off = (16 * warp + (lane & 15)) * 64 + (((lane >> 4) ^ ((lane & 7) >> 1)) << 4);
#pragma unroll 1
    for (int u = 0;; u++) {
      const Unit un{units[u]};
      const int ty = un.type();
      if (ty == U_END) break;
      const bool mc_next = un.mc_next();
      if (ty == U_HQ) {
        r.adv(4);
        if (mc_next) {
          mbar_wait(bars + BAR_GLAST * 8, gph);
          gph ^= 1;
        }
        continue;
      }
      const bool at = ty == U_AT;
      const int n = ty == U_OP ? 64 : 16;
      const int rot = at ? 0 : un.rot();
      float acc0[80], acc1[80];
      if (at && !un.prev_at()) r.adv(3);
      const bool at_end = at && !un.next_at();
      const uint32_t bfull = bars + (at ? BAR_PFULL - 2 : BAR_XFULL) * 8, bempty = bars + (at ? BAR_PEMPTY - 2 : BAR_XEMPTY) * 8;
      uint32_t x = at ? 2 : rot;
      auto mainloop = [&](auto tb) {
        constexpr int TB = decltype(tb)::value;
        constexpr int KB = TB ? 64 : 2;
        mbar_wait(bfull + x * 8, 0);
        mbar_wait(bars + BAR_FO * 8, 0);
        {
          const uint32_t baddr = sbase + OFF_B + (2 + x) * B_BLK;
          const uint64_t da = make_desc(sbase + r.slot * A_SLOT), db = TB ? make_desc_n(baddr) : make_desc(baddr);
          wgmma_fence();
          wgmma_160_init<1, TB>(acc0, da, db);
          wgmma_160_init<1, TB>(acc1, da + 512, db);
#pragma unroll
          for (int kk = 1; kk < 4; kk++) {
            wgmma_160<1, TB>(acc0, da + kk * 128, db + kk * KB);
            wgmma_160<1, TB>(acc1, da + 512 + kk * 128, db + kk * KB);
          }
          wgmma_commit();
        }
        if (TB && opend) {
          fence_async_smem();
          __syncwarp();
          mbar_arrive_n(1, bars + BAR_OSTORE * 8);
        }
#pragma unroll 1
        for (int s = 1; s < n; s++) {
          const uint32_t pslot = r.slot, px = x;
          r.adv((at_end && s >= 14) ? 1 : 2);
          x = at ? 2 + (s & 1) : x_block(s, rot);
          const uint32_t bpar = at ? (s >> 1) & 1 : x_parity(s, rot);
          const uint32_t afull = bars + (BAR_FO + (s & 7)) * 8;
          const bool okb = mbar_test(bfull + x * 8, bpar), oka = mbar_test(afull, (s >> 3) & 1);
          const uint32_t baddr = sbase + OFF_B + (2 + x) * B_BLK;
          const uint64_t da = make_desc(sbase + r.slot * A_SLOT), db = TB ? make_desc_n(baddr) : make_desc(baddr);
          wgmma_wait<0>();
          mbar_arrive_n(1, bempty + px * 8);
          release_a(bars, pslot, s + (at ? 3 : 2) < n ? !at : mc_next, peer, 2);
          if (!okb) mbar_wait(bfull + x * 8, bpar);
          if (!oka) mbar_wait(afull, (s >> 3) & 1);
          if (TB && s == 64 - OP_S_FIRST) mbar_wait(bars + BAR_GLAST * 8, gph);
          wgmma_fence();
#pragma unroll
          for (int kk = 0; kk < 4; kk++) {
            wgmma_160<1, TB>(acc0, da + kk * 128, db + kk * KB);
            wgmma_160<1, TB>(acc1, da + 512 + kk * 128, db + kk * KB);
          }
          wgmma_commit();
        }
      };
      if (ty == U_QP) {
        mainloop(Int<0>{});
        wgmma_wait<0>();
        mbar_arrive_n(1, bempty + x * 8);
        release_a(bars, r.slot, mc_next, peer, 2);
        r.adv(2);
        mbar_wait(bars + BAR_XEMPTY * 8, 1);
        store_block_n(acc0, Q_SCALE, sbase + OFF_B + 2 * B_BLK + st_off);
        mbar_wait(bars + (BAR_XEMPTY + 1) * 8, 1);
        store_block_n(acc1, Q_SCALE, sbase + OFF_B + 3 * B_BLK + st_off);
        fence_async_smem();
        __syncwarp();
        mbar_arrive_n(2, bars + (BAR_QFULL + 1) * 8);
      } else {
        mainloop(Int<1>{});
        if (at) {
          const uint32_t blk = 2 * un.qbuf();
          mbar_wait(bars + BAR_LREADY * 8, lph);
          lph ^= 1;
          float* linv = reinterpret_cast<float*>(smem + OFF_LINV);
          bool bad = false;
          if (lane < 20) {
            const int qp = warp * 20 + lane;
            const float2* lsum = reinterpret_cast<const float2*>(smem + OFF_LSUM) + qp;
            float2 l = lsum[0];
#pragma unroll
            for (int w = 1; w < 8; w++) {
              const float2 v = lsum[w * (SQ / 2)];
              l.x += v.x;
              l.y += v.y;
            }
            bad = !(l.x >= 9.094947e-13f && l.x <= 1.0995116e12f && l.y >= 9.094947e-13f && l.y <= 1.0995116e12f);
            *reinterpret_cast<float2*>(linv + (qp & 3) * 40 + (qp >> 2) * 2) = make_float2(__fdividef(1.f, l.x), __fdividef(1.f, l.y));
          }
          uint32_t anybad;
          asm volatile("{\n.reg .pred p, q;\nsetp.ne.b32 p, %1, 0;\nbar.red.or.pred q, 1, 128, p;\nselp.b32 %0, 1, 0, q;\n}\n"
                       : "=r"(anybad) : "r"((uint32_t)bad) : "memory");
          const float4* lv = reinterpret_cast<const float4*>(linv + (lane & 3) * 40);
          float4 iv[10];
#pragma unroll
          for (int i = 0; i < EP_PRE; i++) iv[i] = lv[i];
          wgmma_wait<0>();
          mbar_arrive_n(1, bempty + x * 8);
          mbar_arrive_n(1, bars + BAR_PDONE * 8);
          release_a(bars, r.slot, mc_next, peer, 2);
          r.adv(at_end ? 1 : 2);
          if (!__any_sync(0xffffffffu, anybad)) {
            const uint32_t addr = sbase + OFF_B + blk * B_BLK + st_off;
#pragma unroll
            for (int j = 0; j < 10; j++) {
              stsm_x4(n_addr(addr, j), pack_bf16(acc0[8 * j] * iv[j].x, acc0[8 * j + 1] * iv[j].y),
                      pack_bf16(acc0[8 * j + 2] * iv[j].x, acc0[8 * j + 3] * iv[j].y),
                      pack_bf16(acc0[8 * j + 4] * iv[j].z, acc0[8 * j + 5] * iv[j].w),
                      pack_bf16(acc0[8 * j + 6] * iv[j].z, acc0[8 * j + 7] * iv[j].w));
              stsm_x4(n_addr(addr, j) + B_BLK, pack_bf16(acc1[8 * j] * iv[j].x, acc1[8 * j + 1] * iv[j].y),
                      pack_bf16(acc1[8 * j + 2] * iv[j].x, acc1[8 * j + 3] * iv[j].y),
                      pack_bf16(acc1[8 * j + 4] * iv[j].z, acc1[8 * j + 5] * iv[j].w),
                      pack_bf16(acc1[8 * j + 6] * iv[j].z, acc1[8 * j + 7] * iv[j].w));
              if (j + EP_PRE < 10) iv[j + EP_PRE] = lv[j + EP_PRE];
            }
          } else {
            const size_t off = (size_t)((un.bp() * 2 + rank) * NH + un.arg()) * SK * DH;
            slow_attention(smem + OFF_B + blk * B_BLK, ptrs.k[br] + off, ptrs.v[br] + off, warp, lane);
          }
          opend = un.next_at();
          if (!opend) {
            fence_async_smem();
            __syncwarp();
            mbar_arrive_n(1, bars + BAR_OSTORE * 8);
          }
        } else {
          wgmma_wait<0>();
          mbar_arrive_n(1, bempty + x * 8);
          mbar_wait(bars + BAR_XEMPTY * 8, 1);
          store_block_t(acc0, sbase + OFF_B + 2 * B_BLK, warp, lane);
          mbar_wait(bars + (BAR_XEMPTY + 1) * 8, 1);
          store_block_t(acc1, sbase + OFF_B + 3 * B_BLK, warp, lane);
          fence_async_smem();
          __syncwarp();
          mbar_arrive_n(2, bars + (BAR_QFULL + 1) * 8);
        }
      }
    }
  } else {
    asm volatile("setmaxnreg.inc.sync.aligned.u32 144;");
    const int si = wg - 1;
    ARing r{0, 0};
    uint32_t qm = 0;
    const uint32_t st_off = (16 * warp + (lane & 15)) * 64 + (((lane >> 4) ^ ((lane & 7) >> 1)) << 4);
#pragma unroll 1
    for (int u = 0;; u++) {
      const Unit un{units[u]};
      const int ty = un.type();
      if (ty == U_END) break;
      const bool mc_next = un.mc_next();
      if (ty == U_AT) {
        const uint32_t qb = un.qbuf();
        if (un.qloaded()) qm ^= 1u << qb;
        mbar_wait(bars + (BAR_QFULL + qb) * 8, ((qm >> qb) & 1) ^ 1);
        const uint64_t dq = make_desc_n(sbase + OFF_B + 2 * qb * B_BLK);
        const uint32_t paddr = sbase + OFF_B + (4 + si) * B_BLK + st_off;
        uint32_t paddr1 = paddr ^ 32;
        asm volatile("" : "+r"(paddr1));
        float l[40];
#pragma unroll
        for (int i = 0; i < 40; i++) l[i] = 0.f;
        if (!un.prev_at()) r.adv(si);
        bool kok = false;
        if (si == 1 && !un.prev_at()) {
          const uint32_t c0 = clock();
          while ((uint32_t)clock() - c0 < COLD_STAGGER) {}
        }
        float* lsum = reinterpret_cast<float*>(smem + OFF_LSUM) + (si * 4 + warp) * SQ + (lane & 24) + 2 * (lane & 3) + ((lane >> 2) & 1);
        auto tile = [&](const int t, auto last) {
          constexpr bool LAST = decltype(last)::value;
          float acc[80];
          if (!kok) mbar_wait(bars + (BAR_FS + si + 2 * (t & 1)) * 8, (t >> 1) & 1);
          const uint64_t dk = make_desc(sbase + r.slot * A_SLOT);
          wgmma_fence();
          wgmma_160_init<0, 1>(acc, dk, dq);
#pragma unroll
          for (int kk = 1; kk < 8; kk++)
            wgmma_160<0, 1>(acc, dk + (kk >> 2) * 512 + (kk & 3) * 2, dq + (kk >> 2) * (B_BLK / 16) + (kk & 3) * 64);
          wgmma_commit();
          mbar_arrive_n(kok ? 1u : 0u, bars + (BAR_PFULL + si) * 8);
          wgmma_wait<0>();
          release_a(bars, r.slot, LAST ? mc_next : false, peer, 2);
          r.adv((t == 0 && !un.prev_at()) ? 2 + si : ((LAST && !un.next_at()) ? 6 - 2 * si : 4));
          auto expo = [&](int j) {
#pragma unroll
            for (int i = 0; i < 8; i++) acc[8 * j + i] = ex2(acc[8 * j + i]);
          };
          uint32_t pk[40];
          auto sums = [&](int c) {
            float* v = l + 8 * c;
            const bool h4 = lane & 16, h3 = lane & 8, h2 = lane & 4;
#pragma unroll
            for (int i = 0; i < 4; i++) v[i] = (h4 ? v[i + 4] : v[i]) + __shfl_xor_sync(0xffffffffu, h4 ? v[i] : v[i + 4], 16);
#pragma unroll
            for (int i = 0; i < 2; i++) v[i] = (h3 ? v[i + 2] : v[i]) + __shfl_xor_sync(0xffffffffu, h3 ? v[i] : v[i + 2], 8);
            lsum[32 * c] = (h2 ? v[1] : v[0]) + __shfl_xor_sync(0xffffffffu, h2 ? v[0] : v[1], 4);
          };
          auto reduce = [&](int j) {
            l[4 * j] += acc[8 * j] + acc[8 * j + 2];
            l[4 * j + 1] += acc[8 * j + 1] + acc[8 * j + 3];
            l[4 * j + 2] += acc[8 * j + 4] + acc[8 * j + 6];
            l[4 * j + 3] += acc[8 * j + 5] + acc[8 * j + 7];
#pragma unroll
            for (int i = 0; i < 4; i++) pk[4 * j + i] = pack_bf16(acc[8 * j + 2 * i], acc[8 * j + 2 * i + 1]);
            if (LAST && (j & 1) && j < 2 * L_EARLY) sums(j >> 1);
          };
          auto store = [&](int j) { stsm_x4((j & 1 ? paddr1 : paddr) + (j >> 1) * 4096, pk[4 * j], pk[4 * j + 1], pk[4 * j + 2], pk[4 * j + 3]); };
#pragma unroll
          for (int j = 0; j < SM_A; j++) expo(j);
          sched_fence(zero);
#pragma unroll
          for (int j = SM_A; j < SM_B; j++) expo(j);
#pragma unroll
          for (int j = 0; j < SM_A; j++) reduce(j);
          mbar_wait(bars + ((t == 0 && !un.prev_at() ? BAR_XEMPTY + 2 : BAR_PEMPTY) + si) * 8, (t & 1) ^ 1);
#pragma unroll
          for (int j = 0; j < SM_A; j++) store(j);
#pragma unroll
          for (int j = SM_B; j < 10; j++) expo(j);
#pragma unroll
          for (int j = SM_A; j < SM_B; j++) { reduce(j); store(j); }
          if (SM_B < 10) sched_fence(zero);
#pragma unroll
          for (int j = SM_B; j < 10; j++) { reduce(j); store(j); }
          kok = !LAST && mbar_test(bars + (BAR_FS + si + 2 * ((t + 1) & 1)) * 8, ((t + 1) >> 1) & 1);
          fence_async_smem();
          __syncwarp();
          mbar_arrive_n(kok ? 0u : 1u, bars + (BAR_PFULL + si) * 8);
          if (LAST) {
#pragma unroll
            for (int c = L_EARLY; c < 5; c++) sums(c);
            __syncwarp();
            mbar_arrive_n(1, bars + BAR_LREADY * 8);
          }
        };
#pragma unroll 1
        for (int t = 0; t < 7; t++) tile(t, Int<0>{});
        tile(7, Int<1>{});
      } else {
        float acc[80];
        const int n = ty == U_OP ? 64 : 16;
        const int rot = un.rot();
        const bool hq = ty == U_HQ;
        const uint32_t xcnt = hq ? 2 - si : 1, astep = hq ? 1 : 2;
        r.adv(astep - 1);
        uint32_t x = rot;
        auto mainloop = [&](auto tb) {
          constexpr int TB = decltype(tb)::value;
          constexpr int KB = TB ? 64 : 2;
          mbar_wait(bars + (BAR_XFULL + x) * 8, 0);
          mbar_wait(bars + ((hq && un.keep0()) ? BAR_FS : BAR_FG) * 8, 0);
          {
            const uint32_t baddr = sbase + OFF_B + (2 + x) * B_BLK;
            const uint64_t da = make_desc(sbase + r.slot * A_SLOT + si * 8192), db = TB ? make_desc_n(baddr) : make_desc(baddr);
            wgmma_fence();
            wgmma_160_init<1, TB>(acc, da, db);
#pragma unroll
            for (int kk = 1; kk < 4; kk++) wgmma_160<1, TB>(acc, da + kk * 128, db + kk * KB);
            wgmma_commit();
          }
#pragma unroll 1
          for (int s = 1; s < n; s++) {
            const uint32_t pslot = r.slot, px = x;
            r.adv(astep);
            x = x_block(s, rot);
            const uint32_t bpar = x_parity(s, rot);
            const uint32_t afull = bars + (((hq && !(s & 4) == un.keep0()) ? BAR_FS : BAR_FG) + (s & 3)) * 8, apar = (s >> (hq ? 3 : 2)) & 1;
            const bool okb = mbar_test(bars + (BAR_XFULL + x) * 8, bpar), oka = mbar_test(afull, apar);
            const uint32_t baddr = sbase + OFF_B + (2 + x) * B_BLK;
            const uint64_t da = make_desc(sbase + r.slot * A_SLOT + si * 8192), db = TB ? make_desc_n(baddr) : make_desc(baddr);
            wgmma_wait<0>();
            mbar_arrive_n(xcnt, bars + (BAR_XEMPTY + px) * 8);
            release_a(bars, pslot, astep * s - 1 + NA < astep * n ? true : mc_next, peer, 1);
            if (!okb) mbar_wait(bars + (BAR_XFULL + x) * 8, bpar);
            if (!oka) mbar_wait(afull, apar);
            wgmma_fence();
#pragma unroll
            for (int kk = 0; kk < 4; kk++) wgmma_160<1, TB>(acc, da + kk * 128, db + kk * KB);
            wgmma_commit();
          }
          mbar_arrive_n((TB || (hq && mc_next)) ? 1u : 0u, bars + BAR_GLAST * 8);
          wgmma_wait<0>();
          mbar_arrive_n(xcnt, bars + (BAR_XEMPTY + x) * 8);
          release_a(bars, r.slot, mc_next, peer, 1);
          r.adv(1);
          mbar_wait(bars + BAR_QEMPTY * 8, (qm & 1) ^ 1);
        };
        if (ty != U_OP) {
          mainloop(Int<0>{});
          store_block_n(acc, Q_SCALE, sbase + OFF_B + si * B_BLK + st_off);
        } else {
          mainloop(Int<1>{});
          store_block_t(acc, sbase + OFF_B + si * B_BLK, warp, lane);
        }
        fence_async_smem();
        __syncwarp();
        mbar_arrive_n(1, bars + BAR_QFULL * 8);
        qm ^= hq ? 1 : 3;
      }
    }
  }
}

typedef CUresult (*EncodeFn)(CUtensorMap*, CUtensorMapDataType, cuuint32_t, void*, const cuuint64_t*, const cuuint64_t*,
                             const cuuint32_t*, const cuuint32_t*, CUtensorMapInterleave, CUtensorMapSwizzle,
                             CUtensorMapL2promotion, CUtensorMapFloatOOBfill);

void make_map_2d(EncodeFn enc, CUtensorMap* m, const void* p, uint64_t cols, uint64_t rows, uint32_t box_rows) {
  cuuint64_t dims[2] = {cols, rows}, strides[1] = {cols * 2};
  cuuint32_t box[2] = {64, box_rows}, es[2] = {1, 1};
  enc(m, CU_TENSOR_MAP_DATA_TYPE_BFLOAT16, 2, const_cast<void*>(p), dims, strides, box, es, CU_TENSOR_MAP_INTERLEAVE_NONE,
      CU_TENSOR_MAP_SWIZZLE_128B, CU_TENSOR_MAP_L2_PROMOTION_L2_128B, CU_TENSOR_MAP_FLOAT_OOB_FILL_NONE);
}
void make_map_kv(EncodeFn enc, CUtensorMap* m, const void* p) {
  cuuint64_t dims[3] = {64, (cuuint64_t)NB * NH * SK, 2}, strides[2] = {DH * 2, 128};
  cuuint32_t box[3] = {64, 64, 2}, es[3] = {1, 1, 1};
  enc(m, CU_TENSOR_MAP_DATA_TYPE_BFLOAT16, 3, const_cast<void*>(p), dims, strides, box, es, CU_TENSOR_MAP_INTERLEAVE_NONE,
      CU_TENSOR_MAP_SWIZZLE_128B, CU_TENSOR_MAP_L2_PROMOTION_L2_128B, CU_TENSOR_MAP_FLOAT_OOB_FILL_NONE);
}

void make_map_lines(EncodeFn enc, CUtensorMap* m, const void* p) {
  cuuint64_t dims[2] = {64, (cuuint64_t)NB * NH * SK * 2}, strides[1] = {128};
  cuuint32_t box[2] = {8, 128}, es[2] = {1, 1};
  enc(m, CU_TENSOR_MAP_DATA_TYPE_BFLOAT16, 2, const_cast<void*>(p), dims, strides, box, es, CU_TENSOR_MAP_INTERLEAVE_NONE,
      CU_TENSOR_MAP_SWIZZLE_NONE, CU_TENSOR_MAP_L2_PROMOTION_L2_128B, CU_TENSOR_MAP_FLOAT_OOB_FILL_NONE);
}

void make_plan(Plan* p, bool spare) {
  enum { F_QBUF1 = 1 << 10, F_LOAD = 1 << 11, F_KEEP0 = 1 << 12, F_BANK = 1 << 13, F_KEEP1 = 1 << 17 };
  const char* with_spare[9] = {"qqqqo", "haaaaaaa", "qqQao", "haaaaaaa", "Qaqqo", "Kbaaaaaa", "Qaqqo", "Kbaaaaaa", "a"};
  const char* without[9] = {"qqQaxo", "haaaaaaa", "qqQaxo", "haaaaaaa", "hbqqqo", "haaaaaaa", "hbqqqo", "haaaaaaa", ""};
  const char* const* prog = spare ? with_spare : without;
  const int delay_spare[9] = {0, 0, 34, 15, 0, 0, 0, 0, 260}, delay_without[9] = {0, 0, 0, 10, 0, 20, 0, 30, 0};
  const int* delay = spare ? delay_spare : delay_without;
  struct Slot { float t; int a, b; };
  Slot supply[NH], demand[NH];
  int ns = 0, nd = 0, next_pair = 0, next_single = NH - 1;
  int type[9][MAX_UNITS], arg[9][MAX_UNITS], flags[9][MAX_UNITS], len[9];
  float tend[9][MAX_UNITS];
  for (int k = 0; k < MAX_UNITS; k++)
    for (int r = 0; r < 9; r++) {
      if (k == 0) len[r] = (int)strlen(prog[r]);
      if (k >= len[r]) continue;
      const char c = prog[r][k];
      const float t0 = k ? tend[r][k - 1] : delay[r] / 88.f;
      tend[r][k] = t0 + ((c == 'h' || c == 'x') ? 0.6f : 1.f);
      flags[r][k] = k ? 0 : delay[r] << 20;
      if (c == 'q' || c == 'Q' || c == 'K') {
        type[r][k] = U_QP;
        arg[r][k] = next_pair++;
        flags[r][k] |= (c != 'q' ? F_KEEP0 : 0) | (c == 'K' ? F_KEEP1 : 0);
        if (c == 'q') supply[ns++] = {tend[r][k], 2 * arg[r][k], 0};
        if (c != 'K') supply[ns++] = {tend[r][k], 2 * arg[r][k] + 1, 0};
      } else if (c == 'h' || c == 'x') {
        type[r][k] = U_HQ;
        arg[r][k] = next_single--;
        if (c == 'h') flags[r][k] |= F_KEEP0;
        else supply[ns++] = {tend[r][k], arg[r][k], 0};
      } else if (c == 'o') {
        type[r][k] = U_OP;
        arg[r][k] = r >> 1;
        if (spare && !delay[r]) flags[r][k] |= 32 << 20;
      } else {
        type[r][k] = U_AT;
        const char p1 = k > 0 ? prog[r][k - 1] : 0, p2 = k > 1 ? prog[r][k - 2] : 0;
        if (k > 0 && type[r][k - 1] == U_AT && !(flags[r][k - 1] & F_QBUF1)) flags[r][k] |= F_QBUF1;
        if (c == 'b') flags[r][k] |= F_BANK;
        if (p1 == 'h') arg[r][k] = arg[r][k - 1];
        else if (p1 == 'Q' || p1 == 'K') arg[r][k] = 2 * arg[r][k - 1];
        else if (p2 == 'K') arg[r][k] = 2 * arg[r][k - 2] + 1;
        else { flags[r][k] |= F_LOAD; demand[nd++] = {t0, r, k}; }
      }
    }
  auto earlier = [](const Slot& x, const Slot& y) { return x.t < y.t; };
  std::stable_sort(supply, supply + ns, earlier);
  std::stable_sort(demand, demand + nd, earlier);
  for (int i = 0; i < nd; i++) arg[demand[i].a][demand[i].b] = supply[i].a;
  Slot done[NH];
  int ndone = 0;
  for (int role = 0; role < MAX_ROLES; role++) {
    const int r = role == 32 ? 8 : role & 7, n = role == 32 ? 4 * len[8] : len[r];
    for (int k = 0; k < MAX_UNITS; k++) {
      if (k >= n) { p->unit[role][k] = U_END; continue; }
      const int kk = role == 32 ? 0 : k;
      uint32_t d = type[r][kk] | (arg[r][kk] << 3) | ((role == 32 ? k : role >> 3) << 8) | flags[r][kk];
      if (role == 32 && (k & 1)) d |= F_QBUF1;
      const int prev = k == 0 ? U_END : type[r][role == 32 ? 0 : k - 1], next = k + 1 == n ? U_END : type[r][role == 32 ? 0 : k + 1];
      if (type[r][kk] != U_AT && prev == U_QP) d |= 1u << 14;
      if (prev == U_AT) d |= 1u << 15;
      if (next != U_END) d |= 1u << (next != U_AT ? 16 : 18);
      p->unit[role][k] = d;
      if (type[r][kk] == U_AT && (role < 8 || (role == 32 && k == 3))) done[ndone++] = {tend[r][kk] + (role == 32 ? 3.f : 0.f), arg[r][kk], 0};
    }
  }
  std::stable_sort(done, done + NH, earlier);
  for (int i = 0; i < NH; i++) p->op_head[i] = (uint8_t)done[i].a;
}

}

extern "C" void kernel_launch(void* const* d_in, const int* in_sizes, int n_in, void* d_out, int out_size) {
  (void)in_sizes; (void)n_in; (void)out_size;
  void* fn = nullptr;
  cudaDriverEntryPointQueryResult qr;
  cudaGetDriverEntryPoint("cuTensorMapEncodeTiled", &fn, cudaEnableDefault, &qr);
  EncodeFn enc = reinterpret_cast<EncodeFn>(fn);
  Maps maps;
  Ptrs ptrs;
  for (int br = 0; br < 2; br++) {
    void* const* in = d_in + 5 * br;
    make_map_2d(enc, &maps.x[br], in[0], DM, NB * SQ, SQ);
    make_map_kv(enc, &maps.k[br], in[1]);
    make_map_kv(enc, &maps.v[br], in[2]);
    make_map_lines(enc, &maps.kline[br], in[1]);
    make_map_lines(enc, &maps.vline[br], in[2]);
    make_map_2d(enc, &maps.wq[br], in[3], NH * DH, DM, 64);
    make_map_2d(enc, &maps.wo[br], in[4], DM, NH * DH, 64);
    ptrs.k[br] = static_cast<const __nv_bfloat16*>(in[1]);
    ptrs.v[br] = static_cast<const __nv_bfloat16*>(in[2]);
  }
  void* sym = nullptr;
  cudaGetSymbolAddress(&sym, g_scratch);
  ptrs.scratch = reinterpret_cast<uint8_t*>((reinterpret_cast<uintptr_t>(sym) + PAGE - 1) & ~(uintptr_t)(PAGE - 1));
  make_map_2d(enc, &maps.out, d_out, 2 * DM, NB * SQ, SQ);
  cudaFuncSetAttribute(mha2_kernel, cudaFuncAttributeMaxDynamicSharedMemorySize, SMEM_BYTES);
  cudaLaunchConfig_t cfg = {};
  cfg.gridDim = 132;
  cfg.blockDim = 512;
  cfg.dynamicSmemBytes = SMEM_BYTES;
  int ncl = 0;
  cudaOccupancyMaxActiveClusters(&ncl, mha2_kernel, &cfg);
  ncl = ncl >= 66 ? 66 : 64;
  Plan plan;
  make_plan(&plan, ncl == 66);
  mha2_kernel<<<2 * ncl, 512, SMEM_BYTES, cudaStreamPerThread>>>(ptrs, plan, maps);
}
```

```cpp
#include <cuda_runtime.h>
#include <cuda_bf16.h>
#include <cuda.h>
#include <stdint.h>
#include <string.h>
#include <algorithm>

namespace {

constexpr int SQ = 160, DM = 1024, NH = 32, SK = 1024, DH = 128, NB = 8;
constexpr int A_SLOT = 16384, NA = 6;
constexpr int B_BLK = 20480;
constexpr int OFF_B = NA * A_SLOT;
constexpr int OFF_LSUM = OFF_B + 6 * B_BLK;
constexpr int OFF_LINV = OFF_LSUM + 8 * SQ * 4;
constexpr int OFF_BAR = OFF_LINV + SQ * 4;
constexpr int OFF_SINK = OFF_BAR + 640 + 1024;
constexpr int SMEM_BYTES = OFF_SINK + 2048 + 1024;
constexpr int BAR_FS = 0;
constexpr int BAR_AEMPTY = 6;
constexpr int BAR_XFULL = 12, BAR_XEMPTY = 16;
constexpr int BAR_PFULL = 20, BAR_PEMPTY = 22;
constexpr int BAR_QFULL = 24, BAR_QEMPTY = 26;
constexpr int BAR_LREADY = 28, BAR_OSTORE = 29, BAR_PDONE = 30;
constexpr int BAR_REMPTY = 31;
constexpr int BAR_FG = 41;
constexpr int BAR_BANK = 45, BAR_GLAST = 46;
constexpr int BAR_FO = 47;
constexpr int BAR_ORD = 55;
constexpr float Q_SCALE = 0.08838834764831845f * 1.4426950408889634f;
constexpr uint32_t SPIN_LIMIT = 1u << 26;
constexpr int DYN = 4;

constexpr int SM_A = 4;
constexpr int SM_B = 7;
constexpr int L_EARLY = 2;
constexpr int EP_PRE = 3;
constexpr int OP_S_FIRST = 2;
constexpr int QP_S_FIRST = 1;
constexpr int COLD_STAGGER = 250;
constexpr int BANK_N = 13;
constexpr int BANK_FIRST = 3;
constexpr int BANK_DELAY = 700;
constexpr int BANK_PACE = 330;

struct Maps {
  CUtensorMap x[2], wq[2], wo[2], k[2], v[2], kline[2], vline[2], out;
};
struct Ptrs {
  uint8_t* scratch;
  const __nv_bfloat16* k[2];
  const __nv_bfloat16* v[2];
};

constexpr int PAGE = 2 << 20, SLOTS_PER_PAGE = 25, SLOT_SPAN = 81920, PROBE_OFF = SLOTS_PER_PAGE * SLOT_SPAN;
constexpr uint32_t PART_MASK = (1u << 13) | (1u << 16) | (1u << 17) | (1u << 19);
__device__ uint4 g_scratch[22 * (PAGE / 16)];

__device__ __forceinline__ uint32_t smem_u32(const void* p) { return (uint32_t)__cvta_generic_to_shared(p); }
__device__ __forceinline__ bool elect_one() {
  uint32_t p;
  asm volatile("{\n.reg .pred p;\nelect.sync _|p, 0xffffffff;\nselp.b32 %0, 1, 0, p;\n}\n" : "=r"(p));
  return p;
}
__device__ __forceinline__ void mbar_init(uint32_t bar, uint32_t cnt) {
  asm volatile("mbarrier.init.shared::cta.b64 [%0], %1;" ::"r"(bar), "r"(cnt));
}
__device__ __forceinline__ void mbar_arrive_expect_tx(uint32_t bar, uint32_t bytes) {
  asm volatile("mbarrier.arrive.expect_tx.shared::cta.b64 _, [%0], %1;" ::"r"(bar), "r"(bytes) : "memory");
}
__device__ __forceinline__ void mbar_expect_tx(uint32_t bar, uint32_t bytes) {
  asm volatile("mbarrier.expect_tx.relaxed.cta.shared::cta.b64 [%0], %1;" ::"r"(bar), "r"(bytes) : "memory");
}
__device__ __forceinline__ void mbar_arrive(uint32_t bar, uint32_t cnt) {
  asm volatile("mbarrier.arrive.shared::cta.b64 _, [%0], %1;" ::"r"(bar), "r"(cnt) : "memory");
}
__device__ __forceinline__ void mbar_arrive_n(uint32_t n, uint32_t bar) {
  asm volatile("{\n.reg .pred p;\n.reg .b32 l;\nmov.u32 l, %%laneid;\nsetp.lt.u32 p, l, %1;\n"
               "@p mbarrier.arrive.shared::cta.b64 _, [%0];\n}\n" ::"r"(bar), "r"(n) : "memory");
}
__device__ __forceinline__ void mbar_arrive_remote_n(uint32_t n, uint32_t bar, uint32_t cta) {
  asm volatile(
      "{\n.reg .pred p;\n.reg .b32 ra, l;\nmov.u32 l, %%laneid;\nsetp.lt.u32 p, l, %2;\nmapa.shared::cluster.u32 ra, %0, %1;\n"
      "@p mbarrier.arrive.shared::cluster.b64 _, [ra];\n}\n" ::"r"(bar), "r"(cta), "r"(n) : "memory");
}
__device__ __forceinline__ void mbar_wait(uint32_t bar, uint32_t parity) {
  asm volatile(
      "{\n.reg .pred p;\n.reg .b32 n;\nmov.b32 n, 0;\n"
      "WAIT_%=:\n"
      "mbarrier.try_wait.parity.shared::cta.b64 p, [%0], %1;\n"
      "@p bra DONE_%=;\n"
      "add.u32 n, n, 1;\n"
      "setp.lt.u32 p, n, %2;\n"
      "@p bra WAIT_%=;\n"
      "trap;\n"
      "DONE_%=:\n}\n" ::"r"(bar), "r"(parity), "n"(SPIN_LIMIT) : "memory");
}
__device__ __forceinline__ void mbar_wait_sleep(uint32_t bar, uint32_t parity) {
  asm volatile(
      "{\n.reg .pred p;\n.reg .b32 n;\nmov.b32 n, 0;\n"
      "WAIT_%=:\n"
      "mbarrier.try_wait.parity.shared::cta.b64 p, [%0], %1, %3;\n"
      "@p bra DONE_%=;\n"
      "add.u32 n, n, 1;\n"
      "setp.lt.u32 p, n, %2;\n"
      "@p bra WAIT_%=;\n"
      "trap;\n"
      "DONE_%=:\n}\n" ::"r"(bar), "r"(parity), "n"(SPIN_LIMIT >> 4), "n"(4000) : "memory");
}
__device__ __forceinline__ bool mbar_test(uint32_t bar, uint32_t parity) {
  uint32_t ok;
  asm volatile("{\n.reg .pred p;\nmbarrier.test_wait.parity.shared::cta.b64 p, [%1], %2;\nselp.b32 %0, 1, 0, p;\n}\n"
               : "=r"(ok) : "r"(bar), "r"(parity) : "memory");
  return ok;
}
__device__ __forceinline__ void tma_2d(uint32_t dst, const CUtensorMap* m, int c0, int c1, uint32_t bar) {
  asm volatile(
      "cp.async.bulk.tensor.2d.shared::cluster.global.mbarrier::complete_tx::bytes [%0], [%1, {%3, %4}], [%2];" ::"r"(dst),
      "l"(m), "r"(bar), "r"(c0), "r"(c1) : "memory");
}
__device__ __forceinline__ void tma_2d_mc(uint32_t dst, const CUtensorMap* m, int c0, int c1, uint32_t bar, uint64_t pol) {
  asm volatile(
      "cp.async.bulk.tensor.2d.shared::cluster.global.mbarrier::complete_tx::bytes.multicast::cluster.L2::cache_hint"
      " [%0], [%1, {%3, %4}], [%2], %5, %6;" ::"r"(dst), "l"(m), "r"(bar), "r"(c0), "r"(c1), "h"((uint16_t)3), "l"(pol) : "memory");
}
__device__ __forceinline__ void tma_3d_hint(uint32_t dst, const CUtensorMap* m, int c1, uint32_t bar, uint64_t pol) {
  asm volatile(
      "cp.async.bulk.tensor.3d.shared::cluster.global.mbarrier::complete_tx::bytes.L2::cache_hint"
      " [%0], [%1, {%4, %3, %4}], [%2], %5;" ::"r"(dst), "l"(m), "r"(bar), "r"(c1), "r"(0), "l"(pol) : "memory");
}
__device__ __forceinline__ void tma_store_2d(const CUtensorMap* m, int c0, int c1, uint32_t src) {
  asm volatile("cp.async.bulk.tensor.2d.global.shared::cta.bulk_group [%0, {%2, %3}], [%1];" ::"l"(m), "r"(src), "r"(c0),
               "r"(c1) : "memory");
}
__device__ __forceinline__ void bulk_g2s(uint32_t dst, const void* src, uint32_t bytes, uint32_t bar) {
  asm volatile("cp.async.bulk.shared::cluster.global.mbarrier::complete_tx::bytes [%0], [%1], %2, [%3];" ::"r"(dst),
               "l"(src), "r"(bytes), "r"(bar) : "memory");
}
__device__ __forceinline__ void bulk_s2g(void* dst, uint32_t src, uint32_t bytes) {
  asm volatile("cp.async.bulk.global.shared::cta.bulk_group [%0], [%1], %2;" ::"l"(dst), "r"(src), "r"(bytes) : "memory");
}
__device__ __forceinline__ void bulk_commit() { asm volatile("cp.async.bulk.commit_group;" ::: "memory"); }
template <int N> __device__ __forceinline__ void bulk_wait_read() { asm volatile("cp.async.bulk.wait_group.read %0;" ::"n"(N) : "memory"); }
template <int N> __device__ __forceinline__ void bulk_wait() { asm volatile("cp.async.bulk.wait_group %0;" ::"n"(N) : "memory"); }
__device__ __forceinline__ void fence_async_smem() { asm volatile("fence.proxy.async.shared::cta;" ::: "memory"); }
__device__ __forceinline__ void fence_async_global() { asm volatile("fence.proxy.async.global;" ::: "memory"); }
__device__ __forceinline__ void wgmma_fence() { asm volatile("wgmma.fence.sync.aligned;" ::: "memory"); }
__device__ __forceinline__ void wgmma_commit() { asm volatile("wgmma.commit_group.sync.aligned;" ::: "memory"); }
template <int N> __device__ __forceinline__ void wgmma_wait() { asm volatile("wgmma.wait_group.sync.aligned %0;" ::"n"(N) : "memory"); }
__device__ __forceinline__ uint64_t make_desc(uint32_t addr) {
  return (uint64_t)((addr & 0x3FFFF) >> 4) | ((uint64_t)1 << 16) | ((uint64_t)64 << 32) | ((uint64_t)1 << 62);
}
__device__ __forceinline__ uint64_t make_desc_n(uint32_t addr) {
  return (uint64_t)((addr & 0x3FFFF) >> 4) | ((uint64_t)256 << 16) | ((uint64_t)32 << 32) | ((uint64_t)2 << 62);
}
__device__ __forceinline__ float ex2(float x) {
  float y;
  asm volatile("ex2.approx.ftz.f32 %0, %1;" : "=f"(y) : "f"(x));
  return y;
}
__device__ __forceinline__ void sched_fence(uint32_t zero) {
  asm volatile("{\n.reg .pred p;\nsetp.eq.b32 p, %0, 0;\nFENCE_%=:\n@p bra.uni FDONE_%=;\nnanosleep.u32 1;\nbra.uni FENCE_%=;\nFDONE_%=:\n}\n" ::"r"(zero) : "memory");
}
__device__ __forceinline__ uint32_t pack_bf16(float lo, float hi) {
  uint32_t r;
  asm("cvt.rn.bf16x2.f32 %0, %1, %2;" : "=r"(r) : "f"(hi), "f"(lo));
  return r;
}
__device__ __forceinline__ void stsm_x4_t(uint32_t addr, uint32_t r0, uint32_t r1, uint32_t r2, uint32_t r3) {
  asm volatile("stmatrix.sync.aligned.m8n8.x4.trans.shared.b16 [%0], {%1, %2, %3, %4};" ::"r"(addr), "r"(r0), "r"(r1),
               "r"(r2), "r"(r3) : "memory");
}
__device__ __forceinline__ void stsm_x4(uint32_t addr, uint32_t r0, uint32_t r1, uint32_t r2, uint32_t r3) {
  asm volatile("stmatrix.sync.aligned.m8n8.x4.shared.b16 [%0], {%1, %2, %3, %4};" ::"r"(addr), "r"(r0), "r"(r1), "r"(r2),
               "r"(r3) : "memory");
}
__device__ __forceinline__ uint32_t wait_flag(const uint32_t* f) {
  uint32_t v, n = 0;
  while (true) {
    asm volatile("ld.acquire.gpu.global.u32 %0, [%1];" : "=r"(v) : "l"(f) : "memory");
    if (v & 4) break;
    if (++n > (SPIN_LIMIT >> 2)) __trap();
    __nanosleep(32);
  }
  fence_async_global();
  return __shfl_sync(0xffffffffu, v, 0);
}

__device__ __forceinline__ uint32_t slot_off(uint32_t slot) {
  return (slot / SLOTS_PER_PAGE) * PAGE + (slot % SLOTS_PER_PAGE) * SLOT_SPAN;
}
__device__ __forceinline__ uint32_t piece_off(uint32_t off, uint32_t sel) {
  return off + (((__popc(off & PART_MASK) ^ sel) & 1) << 12);
}
__device__ __forceinline__ uint32_t local_selector(uint8_t* page, uint32_t pair, uint32_t id, int lane, bool fill) {
  const uint32_t off = PROBE_OFF + pair * 8192;
  uint8_t *p0 = page + piece_off(off, 0) + id * 32, *p1 = page + piece_off(off, 1) + id * 32;
  if (fill && lane < 4) asm volatile("st.global.v4.u32 [%0], {0, 0, 0, 0};" ::"l"((lane & 2 ? p1 : p0) + (lane & 1) * 16) : "memory");
  __syncwarp();
  uint32_t t1 = 0, t2 = 0;
  if (lane == 0)
    asm volatile(
        "{\n.reg .b32 a, b;\n"
        "atom.relaxed.gpu.global.exch.b32 a, [%2], 1;\natom.relaxed.gpu.global.exch.b32 b, [%3], 1;\n"
        "{\n.reg .pred p;\nsetp.eq.u32 p, a, 0xffffffff;\n@p trap;\n}\n"
        "mov.u32 %0, %%clock;\n"
        "{\n.reg .pred p;\nsetp.eq.u32 p, b, 0xffffffff;\n@p trap;\n}\n"
        "mov.u32 %1, %%clock;\n}\n"
        : "=r"(t1), "=r"(t2) : "l"(p0), "l"(p1) : "memory");
  return __shfl_sync(0xffffffffu, t2 - t1 > 100 ? 0u : 1u, 0);
}

template <int TA, int TB>
__device__ __forceinline__ void wgmma_160(float (&d)[80], uint64_t descA, uint64_t descB) {
  asm volatile(
      "wgmma.mma_async.sync.aligned.m64n160k16.f32.bf16.bf16 {"
      "%0, %1, %2, %3, %4, %5, %6, %7, %8, %9, %10, %11, %12, %13, %14, %15, "
      "%16, %17, %18, %19, %20, %21, %22, %23, %24, %25, %26, %27, %28, %29, %30, %31, "
      "%32, %33, %34, %35, %36, %37, %38, %39, %40, %41, %42, %43, %44, %45, %46, %47, "
      "%48, %49, %50, %51, %52, %53, %54, %55, %56, %57, %58, %59, %60, %61, %62, %63, "
      "%64, %65, %66, %67, %68, %69, %70, %71, %72, %73, %74, %75, %76, %77, %78, %79}, "
      "%80, %81, 1, 1, 1, %82, %83;\n"
      : "+f"(d[0]), "+f"(d[1]), "+f"(d[2]), "+f"(d[3]), "+f"(d[4]), "+f"(d[5]), "+f"(d[6]), "+f"(d[7]),
        "+f"(d[8]), "+f"(d[9]), "+f"(d[10]), "+f"(d[11]), "+f"(d[12]), "+f"(d[13]), "+f"(d[14]), "+f"(d[15]),
        "+f"(d[16]), "+f"(d[17]), "+f"(d[18]), "+f"(d[19]), "+f"(d[20]), "+f"(d[21]), "+f"(d[22]), "+f"(d[23]),
        "+f"(d[24]), "+f"(d[25]), "+f"(d[26]), "+f"(d[27]), "+f"(d[28]), "+f"(d[29]), "+f"(d[30]), "+f"(d[31]),
        "+f"(d[32]), "+f"(d[33]), "+f"(d[34]), "+f"(d[35]), "+f"(d[36]), "+f"(d[37]), "+f"(d[38]), "+f"(d[39]),
        "+f"(d[40]), "+f"(d[41]), "+f"(d[42]), "+f"(d[43]), "+f"(d[44]), "+f"(d[45]), "+f"(d[46]), "+f"(d[47]),
        "+f"(d[48]), "+f"(d[49]), "+f"(d[50]), "+f"(d[51]), "+f"(d[52]), "+f"(d[53]), "+f"(d[54]), "+f"(d[55]),
        "+f"(d[56]), "+f"(d[57]), "+f"(d[58]), "+f"(d[59]), "+f"(d[60]), "+f"(d[61]), "+f"(d[62]), "+f"(d[63]),
        "+f"(d[64]), "+f"(d[65]), "+f"(d[66]), "+f"(d[67]), "+f"(d[68]), "+f"(d[69]), "+f"(d[70]), "+f"(d[71]),
        "+f"(d[72]), "+f"(d[73]), "+f"(d[74]), "+f"(d[75]), "+f"(d[76]), "+f"(d[77]), "+f"(d[78]), "+f"(d[79])
      : "l"(descA), "l"(descB), "n"(TA), "n"(TB));
}
template <int TA, int TB>
__device__ __forceinline__ void wgmma_160_init(float (&d)[80], uint64_t descA, uint64_t descB) {
  asm volatile(
      "wgmma.mma_async.sync.aligned.m64n160k16.f32.bf16.bf16 {"
      "%0, %1, %2, %3, %4, %5, %6, %7, %8, %9, %10, %11, %12, %13, %14, %15, "
      "%16, %17, %18, %19, %20, %21, %22, %23, %24, %25, %26, %27, %28, %29, %30, %31, "
      "%32, %33, %34, %35, %36, %37, %38, %39, %40, %41, %42, %43, %44, %45, %46, %47, "
      "%48, %49, %50, %51, %52, %53, %54, %55, %56, %57, %58, %59, %60, %61, %62, %63, "
      "%64, %65, %66, %67, %68, %69, %70, %71, %72, %73, %74, %75, %76, %77, %78, %79}, "
      "%80, %81, 0, 1, 1, %82, %83;\n"
      : "=f"(d[0]), "=f"(d[1]), "=f"(d[2]), "=f"(d[3]), "=f"(d[4]), "=f"(d[5]), "=f"(d[6]), "=f"(d[7]),
        "=f"(d[8]), "=f"(d[9]), "=f"(d[10]), "=f"(d[11]), "=f"(d[12]), "=f"(d[13]), "=f"(d[14]), "=f"(d[15]),
        "=f"(d[16]), "=f"(d[17]), "=f"(d[18]), "=f"(d[19]), "=f"(d[20]), "=f"(d[21]), "=f"(d[22]), "=f"(d[23]),
        "=f"(d[24]), "=f"(d[25]), "=f"(d[26]), "=f"(d[27]), "=f"(d[28]), "=f"(d[29]), "=f"(d[30]), "=f"(d[31]),
        "=f"(d[32]), "=f"(d[33]), "=f"(d[34]), "=f"(d[35]), "=f"(d[36]), "=f"(d[37]), "=f"(d[38]), "=f"(d[39]),
        "=f"(d[40]), "=f"(d[41]), "=f"(d[42]), "=f"(d[43]), "=f"(d[44]), "=f"(d[45]), "=f"(d[46]), "=f"(d[47]),
        "=f"(d[48]), "=f"(d[49]), "=f"(d[50]), "=f"(d[51]), "=f"(d[52]), "=f"(d[53]), "=f"(d[54]), "=f"(d[55]),
        "=f"(d[56]), "=f"(d[57]), "=f"(d[58]), "=f"(d[59]), "=f"(d[60]), "=f"(d[61]), "=f"(d[62]), "=f"(d[63]),
        "=f"(d[64]), "=f"(d[65]), "=f"(d[66]), "=f"(d[67]), "=f"(d[68]), "=f"(d[69]), "=f"(d[70]), "=f"(d[71]),
        "=f"(d[72]), "=f"(d[73]), "=f"(d[74]), "=f"(d[75]), "=f"(d[76]), "=f"(d[77]), "=f"(d[78]), "=f"(d[79])
      : "l"(descA), "l"(descB), "n"(TA), "n"(TB));
}

enum { U_QP = 0, U_AT = 1, U_OP = 2, U_HQ = 3, U_END = 4 };
constexpr int MAX_UNITS = 9, MAX_ROLES = 33;
struct Plan {
  uint32_t unit[MAX_ROLES][MAX_UNITS];
  uint8_t op_head[NH];
};
struct Unit {
  uint32_t d;
  __device__ __forceinline__ int type() const { return d & 7; }
  __device__ __forceinline__ int arg() const { return (d >> 3) & 31; }
  __device__ __forceinline__ int bp() const { return (d >> 8) & 3; }
  __device__ __forceinline__ int qbuf() const { return (d >> 10) & 1; }
  __device__ __forceinline__ bool qloaded() const { return (d >> 11) & 1; }
  __device__ __forceinline__ bool keep0() const { return (d >> 12) & 1; }
  __device__ __forceinline__ bool keep1() const { return (d >> 17) & 1; }
  __device__ __forceinline__ bool bank() const { return (d >> 13) & 1; }
  __device__ __forceinline__ int rot() const { return (d >> 13) & 2; }
  __device__ __forceinline__ bool prev_at() const { return (d >> 15) & 1; }
  __device__ __forceinline__ uint32_t delay() const { return (d >> 20) * 256; }
  __device__ __forceinline__ bool next_at() const { return (d >> 18) & 1; }
  __device__ __forceinline__ bool mc_next() const { return (d >> 16) & 1; }
};

__device__ __forceinline__ uint32_t x_block(int s, int rot) {
  return (rot && s < 16) ? (0x44e4e4eeu >> (2 * s)) & 3 : (s + rot) & 3;
}
__device__ __forceinline__ uint32_t x_parity(int s, int rot) {
  return (rot && s < 16) ? (0xcf0cu >> s) & 1 : (s >> 2) & 1;
}

template <int V> struct Int { static constexpr int value = V; };

struct ARing {
  uint32_t slot, phase;
  __device__ __forceinline__ void adv(uint32_t n) {
    slot += n;
    if (slot >= NA) { slot -= NA; phase ^= 1; }
  }
};

__device__ __forceinline__ void release_a(uint32_t bars, uint32_t slot, bool next_mc, uint32_t peer, uint32_t cnt) {
  const uint32_t bar = bars + (BAR_AEMPTY + slot) * 8;
  mbar_arrive_n(cnt, bar);
  mbar_arrive_remote_n(next_mc ? cnt : 0u, bar + (BAR_REMPTY - BAR_AEMPTY) * 8, peer);
}

constexpr int OFF_ORD = 480;
__device__ __forceinline__ void send_both(uint32_t bars, int k, uint32_t msg, int lane) {
  if (lane < 2)
    asm volatile(
        "{\n.reg .b32 a, m;\nmapa.shared::cluster.u32 a, %0, %3;\nmapa.shared::cluster.u32 m, %1, %3;\n"
        "st.async.weak.shared::cluster.mbarrier::complete_tx::bytes.b32 [a], %2, [m];\n}\n" ::"r"(bars + OFF_ORD + k * 4),
        "r"(bars + (BAR_ORD + k) * 8), "r"(msg), "r"(lane) : "memory");
  __syncwarp();
}
__device__ __forceinline__ uint32_t read_order(uint32_t bars, int k) {
  uint32_t v;
  asm volatile(
      "{\n.reg .pred p;\n.reg .b32 n;\nmov.b32 n, 0;\n"
      "WAIT_%=:\n"
      "mbarrier.try_wait.parity.acquire.cluster.shared::cta.b64 p, [%1], 0;\n"
      "@p bra DONE_%=;\n"
      "add.u32 n, n, 1;\n"
      "setp.lt.u32 p, n, %3;\n"
      "@p bra WAIT_%=;\n"
      "trap;\n"
      "DONE_%=:\n"
      "ld.volatile.shared.u32 %0, [%2];\n}\n"
      : "=r"(v) : "r"(bars + (BAR_ORD + k) * 8), "r"(bars + OFF_ORD + k * 4), "n"(SPIN_LIMIT) : "memory");
  return __shfl_sync(0xffffffffu, v, 0);
}

__device__ __forceinline__ void store_block_t(const float (&acc)[80], uint32_t blk, int warp, int lane) {
  const uint32_t addr = blk + ((lane & 7) + ((lane >> 4) << 3)) * 128 + (((2 * warp + ((lane >> 3) & 1)) ^ (lane & 7)) << 4);
#pragma unroll
  for (int j = 0; j < 10; j++) {
    stsm_x4_t(addr + j * 2048, pack_bf16(acc[8 * j], acc[8 * j + 1]), pack_bf16(acc[8 * j + 2], acc[8 * j + 3]),
              pack_bf16(acc[8 * j + 4], acc[8 * j + 5]), pack_bf16(acc[8 * j + 6], acc[8 * j + 7]));
  }
}
__device__ __forceinline__ uint32_t n_addr(uint32_t addr0, int j) { return (addr0 ^ ((j & 1) << 5)) + (j >> 1) * 4096; }
__device__ __forceinline__ void store_block_n(const float (&acc)[80], float scale, uint32_t addr0) {
#pragma unroll
  for (int j = 0; j < 10; j++) {
    stsm_x4(n_addr(addr0, j), pack_bf16(acc[8 * j] * scale, acc[8 * j + 1] * scale),
            pack_bf16(acc[8 * j + 2] * scale, acc[8 * j + 3] * scale),
            pack_bf16(acc[8 * j + 4] * scale, acc[8 * j + 5] * scale),
            pack_bf16(acc[8 * j + 6] * scale, acc[8 * j + 7] * scale));
  }
}

__device__ __forceinline__ void slow_attention(uint8_t* qblk, const __nv_bfloat16* kp, const __nv_bfloat16* vp, int warp, int lane) {
  auto elem = [&](int d, int q) {
    return reinterpret_cast<__nv_bfloat16*>(qblk + (d >> 6) * B_BLK + (q >> 5) * 4096 + (d & 63) * 64 +
                                            ((((q >> 3) & 3) ^ ((d >> 1) & 3)) << 4) + (q & 7) * 2);
  };
  auto unpack = [](uint2 w, float (&f)[4]) {
    f[0] = __uint_as_float(w.x << 16);
    f[1] = __uint_as_float(w.x & 0xffff0000u);
    f[2] = __uint_as_float(w.y << 16);
    f[3] = __uint_as_float(w.y & 0xffff0000u);
  };
#pragma unroll 1
  for (int q0 = 4 * warp; q0 < SQ; q0 += 16) {
    float qv[4][4], o[4][4], m[4], l[4];
#pragma unroll
    for (int i = 0; i < 4; i++) {
      m[i] = -INFINITY;
      l[i] = 0.f;
#pragma unroll
      for (int c = 0; c < 4; c++) {
        qv[i][c] = __bfloat162float(*elem(4 * lane + c, q0 + i));
        o[i][c] = 0.f;
      }
    }
#pragma unroll 2
    for (int k = 0; k < SK; k++) {
      float kf[4], vf[4];
      unpack(*reinterpret_cast<const uint2*>(kp + (size_t)k * DH + lane * 4), kf);
      unpack(*reinterpret_cast<const uint2*>(vp + (size_t)k * DH + lane * 4), vf);
#pragma unroll
      for (int i = 0; i < 4; i++) {
        float s = qv[i][0] * kf[0] + qv[i][1] * kf[1] + qv[i][2] * kf[2] + qv[i][3] * kf[3];
#pragma unroll
        for (int d = 16; d > 0; d >>= 1) s += __shfl_xor_sync(0xffffffffu, s, d);
        const float mn = fmaxf(m[i], s), alpha = exp2f(m[i] - mn), p = exp2f(s - mn);
        m[i] = mn;
        l[i] = l[i] * alpha + p;
#pragma unroll
        for (int c = 0; c < 4; c++) o[i][c] = o[i][c] * alpha + p * vf[c];
      }
    }
#pragma unroll
    for (int i = 0; i < 4; i++)
#pragma unroll
      for (int c = 0; c < 4; c++) *elem(4 * lane + c, q0 + i) = __float2bfloat16(o[i][c] / l[i]);
  }
}

__global__ void __cluster_dims__(2, 1, 1) __launch_bounds__(512, 1)
mha2_kernel(const __grid_constant__ Ptrs ptrs, const __grid_constant__ Plan plan, const __grid_constant__ Maps maps) {
  extern __shared__ uint8_t smem_raw[];
  uint8_t* smem = smem_raw + ((1024 - (smem_u32(smem_raw) & 1023)) & 1023);
  const uint32_t sbase = smem_u32(smem);
  const uint32_t bars = sbase + OFF_BAR;
  const int tid = threadIdx.x, lane = tid & 31;
  const int warp = __shfl_sync(0xffffffffu, (tid >> 5) & 3, 0);
  const uint32_t zero = blockIdx.y;
  const int wg = __shfl_sync(0xffffffffu, tid >> 7, 0);
  const uint32_t rank = blockIdx.x & 1, peer = rank ^ 1;
  uint8_t* const scratch = ptrs.scratch;
  uint32_t* const taken0 = reinterpret_cast<uint32_t*>(scratch + piece_off(PROBE_OFF + 2 * 8192, 0));
  uint32_t* const taken1 = reinterpret_cast<uint32_t*>(scratch + piece_off(PROBE_OFF + 2 * 8192, 1));
  uint32_t role = 0;
  const bool claimer = wg == 3 && warp == 3 && rank == 0;
  if (claimer) {
    asm volatile("barrier.cluster.arrive.relaxed;" ::: "memory");
    local_selector(scratch, 5, blockIdx.x >> 1, lane, true);
    const uint32_t side = local_selector(scratch, 5, blockIdx.x >> 1, lane, false);
    if (lane == 0) {
      const uint32_t ncl = gridDim.x >> 1, half = ncl >> 1;
      const uint32_t t = atomicAdd(side ? taken1 : taken0, 1u);
      role = side * 64 + t;
      if (t >= half) {
        uint32_t v0, v1, n = 0;
        while (true) {
          asm volatile("ld.relaxed.gpu.global.u32 %0, [%1];" : "=r"(v0) : "l"(taken0) : "memory");
          asm volatile("ld.relaxed.gpu.global.u32 %0, [%1];" : "=r"(v1) : "l"(taken1) : "memory");
          if (v0 + v1 >= ncl) break;
          if (++n > (SPIN_LIMIT >> 2)) __trap();
        }
        role = (side ^ 1) * 64 + (side ? v0 : v1) + (t - half);
      }
    }
    role = __shfl_sync(0xffffffffu, role, 0);
  }
  if (tid >= 64 && tid < 64 + (int)(sizeof(Maps) / sizeof(CUtensorMap)))
    asm volatile("prefetch.tensormap [%0];" ::"l"(reinterpret_cast<const CUtensorMap*>(&maps) + (tid - 64)) : "memory");
  if (tid == 0) {
    for (int i = 0; i < NA; i++) {
      mbar_init(bars + (BAR_AEMPTY + i) * 8, 8);
      mbar_init(bars + (BAR_REMPTY + i) * 8, 8);
    }
    for (int i = 0; i < 4; i++) {
      mbar_init(bars + (BAR_XFULL + i) * 8, 1);
      mbar_init(bars + (BAR_FO + i) * 8, 1);
      mbar_init(bars + (BAR_FO + 4 + i) * 8, 1);
      mbar_init(bars + (BAR_FG + i) * 8, 1);
      mbar_init(bars + (BAR_FS + i) * 8, 1);
      mbar_init(bars + (BAR_XEMPTY + i) * 8, 12);
      mbar_init(bars + (BAR_PFULL + i) * 8, 4);
    }
    for (int i = 0; i < 2; i++) {
      mbar_init(bars + (BAR_QFULL + i) * 8, 8);
      mbar_init(bars + (BAR_QEMPTY + i) * 8, 1);
    }
    mbar_init(bars + BAR_PDONE * 8, 4);
    mbar_init(bars + BAR_BANK * 8, 1);
    mbar_init(bars + BAR_GLAST * 8, 8);
    for (int i = 0; i <= DYN; i++) {
      mbar_init(bars + (BAR_ORD + i) * 8, 1);
      mbar_arrive_expect_tx(bars + (BAR_ORD + i) * 8, 4);
    }
    mbar_init(bars + BAR_LREADY * 8, 8);
    mbar_init(bars + BAR_OSTORE * 8, 4);
    asm volatile("fence.mbarrier_init.release.cluster;" ::: "memory");
  }
  if (!claimer) asm volatile("barrier.cluster.arrive.relaxed;" ::: "memory");
  asm volatile("barrier.cluster.wait;" ::: "memory");
  if (claimer) send_both(bars, DYN, role, lane);
  role = read_order(bars, DYN);
  const int br = role >> 6;
  const uint32_t* const units = plan.unit[role & 63];
  uint32_t* const qflag = reinterpret_cast<uint32_t*>(scratch + piece_off(PROBE_OFF + 3 * 8192, br)) - br * NB * NH;
  uint4* const oflag = reinterpret_cast<uint4*>(scratch + piece_off(PROBE_OFF + 4 * 8192, br)) - br * NB * NH;
  const int cta = (role & 63) < 32 ? (br * 32 + (role & 63)) * 2 + rank : 128 + br * 2 + rank;

  if (wg == 3) {
    asm volatile("setmaxnreg.dec.sync.aligned.u32 32;");
    auto pause = [](uint32_t cycles) {
      const uint32_t c0 = clock();
      while ((uint32_t)clock() - c0 < cycles) __nanosleep(50);
    };
    if (warp < 2) pause(Unit{units[0]}.delay());
    if (warp == 0) {
      uint64_t pol;
      asm volatile("createpolicy.fractional.L2::evict_first.b64 %0, 1.0;" : "=l"(pol));
      ARing r{0, 1};
      uint32_t rm = 0x3F;
#pragma unroll 1
      for (int u = 0;; u++) {
        const Unit un{units[u]};
        const int ty = un.type();
        if (ty == U_END) break;
        const int arg = un.arg(), b = un.bp() * 2 + rank;
        if (ty == U_AT) {
          const CUtensorMap *mk = &maps.k[br], *mv = &maps.v[br];
          const int row0 = (b * NH + arg) * SK;
          if (u > 0) pause(un.delay());
          const Unit nx{units[u + 1]};
          const int row_next = ((nx.bp() * 2 + rank) * NH + nx.arg()) * SK - 16 * 64;
#pragma unroll 1
          for (int j = un.prev_at() ? 0 : -2; j < 16; j++) {
            if (j < 14 || un.next_at()) {
              const uint32_t full = bars + (BAR_FS + ((j + 2) & 3)) * 8;
              mbar_wait(bars + (BAR_AEMPTY + r.slot) * 8, r.phase);
              if (elect_one()) {
                mbar_arrive_expect_tx(full, A_SLOT);
                tma_3d_hint(sbase + r.slot * A_SLOT, mk, (j < 14 ? row0 : row_next) + (j + 2) * 64, full, pol);
              }
              r.adv(1);
            }
            if (j >= 0) {
              const uint32_t full = bars + (BAR_FO + (j & 7)) * 8;
              mbar_wait(bars + (BAR_AEMPTY + r.slot) * 8, r.phase);
              if (elect_one()) {
                mbar_arrive_expect_tx(full, A_SLOT);
                tma_3d_hint(sbase + r.slot * A_SLOT, mv, row0 + j * 64, full, pol);
              }
              r.adv(1);
            }
          }
        } else {
          const CUtensorMap* mw = ty == U_OP ? &maps.wo[br] : &maps.wq[br];
          const int col = arg * (ty == U_HQ ? 128 : 256) + rank * 64;
          const int n = ty == U_OP ? 64 : 16;
          int row = 0;
#pragma unroll 1
          for (int s = 0; s < n; s++) {
            if (ty == U_OP && (s & 1) == 0) {
              int hi = s >> 1;
              if (hi >= NH - DYN) hi = NH - DYN + (read_order(bars, hi - (NH - DYN)) & 255);
              row = plan.op_head[hi] * DH;
            }
#pragma unroll 1
            for (int i = ty == U_HQ ? 1 : 0; i < 2; i++) {
              const uint32_t full = bars + (i == 0 ? BAR_FO + (s & 7) : ((ty == U_HQ && !(s & 4) == un.keep0()) ? BAR_FS : BAR_FG) + (s & 3)) * 8;
              mbar_wait(bars + (BAR_AEMPTY + r.slot) * 8, r.phase);
              mbar_wait(bars + (BAR_REMPTY + r.slot) * 8, (rm >> r.slot) & 1);
              rm ^= 1u << r.slot;
              if (elect_one()) {
                mbar_arrive_expect_tx(full, A_SLOT);
                tma_2d_mc(sbase + r.slot * A_SLOT + rank * 8192, mw, col + (i ^ 1) * 128, row, full, pol);
              }
              r.adv(1);
            }
            row += 64;
          }
        }
      }
    } else if (warp == 1) {
      uint32_t qm = 0, pdph = 0;
#pragma unroll 1
      for (int u = 0;; u++) {
        const Unit un{units[u]};
        const int ty = un.type();
        if (ty == U_END) break;
        const int b = un.bp() * 2 + rank, bh0 = (br * NB + b) * NH;
        if (ty == U_AT) {
          if (un.qloaded()) {
            const int slot = bh0 + un.arg(), qb = un.qbuf();
            const uint32_t sel = wait_flag(&qflag[slot]);
            const uint32_t full = bars + (BAR_QFULL + qb) * 8;
            mbar_wait_sleep(bars + (BAR_QEMPTY + qb) * 8, ((qm >> qb) & 1) ^ 1);
            mbar_wait_sleep(bars + BAR_XEMPTY * 8, 1);
            mbar_wait_sleep(bars + (BAR_XEMPTY + 1) * 8, 1);
            if (elect_one()) {
              qflag[slot] = 0;
              mbar_expect_tx(full, 2 * B_BLK);
              mbar_arrive(full, 8);
              const uint32_t off = slot_off(slot);
#pragma unroll 1
              for (int i = 0; i < 10; i++)
                bulk_g2s(sbase + OFF_B + 2 * qb * B_BLK + i * 4096, scratch + piece_off(off + i * 8192, sel), 4096, full);
            }
            qm ^= 1u << qb;
          }
        } else {

          const int n = ty == U_OP ? 64 : 16, rot = un.rot();
          const bool prev_at = un.prev_at();
          uint32_t off = 0, sel = 0, todo = (1u << DYN) - 1;
          uint32_t* flag = nullptr;
#pragma unroll 1
          for (int s = 0; s < n; s++) {
            const int x = x_block(s, rot);
            if (s == 3 && u > 0) pause(un.delay());
            if (ty == U_OP && (s & 1) == 0) {
              int hi = s >> 1;
              if (hi >= NH - DYN) {
                const int k = hi - (NH - DYN);
                uint32_t msg;
                if (rank == 0) {
                  const int c = lane % DYN, rk = (lane / DYN) & 1;
                  const uint32_t* f = reinterpret_cast<const uint32_t*>(&oflag[bh0 + rk * NH + plan.op_head[NH - DYN + c]]) + un.arg();
                  uint32_t v, ready, cnt = 0;
                  while (true) {
                    asm volatile("ld.acquire.gpu.global.u32 %0, [%1];" : "=r"(v) : "l"(f) : "memory");
                    const uint32_t m = __ballot_sync(0xffffffffu, v != 0);
                    ready = m & (m >> DYN) & todo;
                    if (ready) break;
                    if (++cnt > (SPIN_LIMIT >> 2)) __trap();
                  }
                  const int i = __ffs(ready) - 1;
                  todo &= ~(1u << i);
                  msg = i | (__shfl_sync(0xffffffffu, v, i) << 8) | (__shfl_sync(0xffffffffu, v, i + DYN) << 12);
                  send_both(bars, k, msg, lane);
                } else {
                  msg = read_order(bars, k);
                }
                fence_async_global();
                hi = NH - DYN + (msg & 255);
                sel = (msg >> (8 + 4 * rank)) & 7;
              }
              const int slot = bh0 + plan.op_head[hi];
              off = slot_off(slot);
              flag = reinterpret_cast<uint32_t*>(&oflag[slot]) + un.arg();
              if ((s >> 1) < NH - DYN) sel = wait_flag(flag);
            } else if (ty == U_OP) {
              if (!(sel & 4)) wait_flag(flag);
              if (elect_one()) *flag = 0;
            }
            if (s <= 4) {
              if (x == 0) mbar_wait_sleep(bars + (BAR_QEMPTY + 1) * 8, ((qm >> 1) & 1) ^ 1);
              if (s == 2 && prev_at) { mbar_wait_sleep(bars + BAR_PDONE * 8, pdph); pdph ^= 1; }
            }
            const uint32_t full = bars + (BAR_XFULL + x) * 8, dst = sbase + OFF_B + (2 + x) * B_BLK;
            mbar_wait_sleep(bars + (BAR_XEMPTY + x) * 8, x_parity(s, rot) ^ 1);
            if (elect_one()) {
              mbar_arrive_expect_tx(full, B_BLK);
              if (ty != U_OP) {
                tma_2d(dst, &maps.x[br], s * 64, b * SQ, full);
              } else {
#pragma unroll
                for (int i = 0; i < 5; i++)
                  bulk_g2s(dst + i * 4096, scratch + piece_off(off + ((s & 1) * 5 + i) * 8192, sel), 4096, full);
              }
            }
          }
          qm ^= ty == U_HQ ? 1 : 3;
        }
      }
    } else if (warp == 2) {
      uint32_t qm = 0, oph = 0;
      uint32_t known = 0, selmask = 0;
#pragma unroll 1
      for (int i = 0;; i++) {
        const Unit un{units[i >> 1]};
        if (un.type() == U_END) break;
        if (un.type() == U_OP) continue;
        const uint32_t page = ((br * NB + un.bp() * 2 + rank) * NH + (un.type() != U_QP ? un.arg() : 2 * un.arg() + (i & 1))) / SLOTS_PER_PAGE;
        if ((known >> page) & 1) continue;
        uint32_t votes = 0;
#pragma unroll 1
        for (int j = 0; j < 4; j++) {
          const uint32_t v = local_selector(scratch + page * PAGE, cta >> 7, cta & 127, lane, j == 0);
          if (j) votes += v;
        }
        known |= 1u << page;
        selmask |= (votes >> 1) << page;
      }
      auto store_slot = [&](uint32_t slot, uint32_t src, bool urgent) {
        const uint32_t sel = (selmask >> (slot / SLOTS_PER_PAGE)) & 1, off = slot_off(slot);
#pragma unroll 1
        for (int i = 0; i < 10; i++) {
          bulk_s2g(scratch + piece_off(off + i * 8192, sel), src + i * 4096, 4096);
          if (i == 4 && urgent) {
            bulk_commit();
            bulk_wait<0>();
            fence_async_global();
            asm volatile("fence.release.gpu;" ::: "memory");
            asm volatile("st.relaxed.gpu.global.v4.u32 [%0], {%1, %1, %1, %1};" ::"l"(&oflag[slot]), "r"(2 + sel) : "memory");
          }
        }
        bulk_commit();
        return 6 + sel;
      };
#pragma unroll 1
      for (int u = 0; lane == 0; u++) {
        const Unit un{units[u]};
        const int ty = un.type();
        if (ty == U_END) break;
        const int b = un.bp() * 2 + rank, bh0 = (br * NB + b) * NH;
        if (ty == U_AT) {
          const int slot = bh0 + un.arg(), qb = un.qbuf();
          if (un.qloaded()) qm ^= 1u << qb;
          mbar_wait_sleep(bars + BAR_OSTORE * 8, oph);
          oph ^= 1;
          const uint32_t fv = store_slot(slot, sbase + OFF_B + 2 * qb * B_BLK, !un.next_at() && !un.mc_next());
          bulk_wait_read<0>();
          mbar_arrive(bars + (BAR_QEMPTY + qb) * 8, 1);
          bulk_wait<0>();
          fence_async_global();
          asm volatile("fence.release.gpu;" ::: "memory");
          asm volatile("st.relaxed.gpu.global.v4.u32 [%0], {%1, %1, %1, %1};" ::"l"(&oflag[slot]), "r"(fv) : "memory");
        } else if (ty != U_OP) {
          const int slot = bh0 + (ty == U_QP ? 2 : 1) * un.arg();
          const int hi = (ty == U_QP && !un.keep1()) ? 1 : 0, lo = un.keep0() ? 1 : 0;
          uint32_t fv = 0;
#pragma unroll 1
          for (int h = hi; h >= lo; h--) {
            mbar_wait_sleep(bars + (BAR_QFULL + h) * 8, (qm >> h) & 1);
            fv |= store_slot(slot + h, sbase + OFF_B + 2 * h * B_BLK, false) << (4 * h);
            bulk_wait_read<0>();
            mbar_arrive(bars + (BAR_QEMPTY + h) * 8, 1);
          }
          if (hi >= lo) {
            bulk_wait<0>();
            fence_async_global();
            asm volatile("fence.release.gpu;" ::: "memory");
#pragma unroll 1
            for (int h = lo; h <= hi; h++)
              asm volatile("st.relaxed.gpu.global.u32 [%0], %1;" ::"l"(&qflag[slot + h]), "r"((fv >> (4 * h)) & 7) : "memory");
          }
          qm ^= ty == U_QP ? 3 : 1;
        } else {
#pragma unroll 1
          for (int i = 0; i < 4; i++) {
            mbar_wait_sleep(bars + (BAR_QFULL + (i >> 1)) * 8, (qm >> (i >> 1)) & 1);
            tma_store_2d(&maps.out, br * DM + un.arg() * 256 + i * 64, b * SQ, sbase + OFF_B + i * B_BLK);
          }
          bulk_commit();
          bulk_wait_read<0>();
        }
      }
    }
    if (claimer && lane == 0) {
      if (atomicAdd(taken0 + 1, 1) == (gridDim.x >> 1) - 1) {
        taken0[0] = 0;
        taken0[1] = 0;
        taken1[0] = 0;
      }
    }
    __syncwarp();
    if (warp == 3 && Unit{units[1]}.bank()) {
      const int line0 = ((Unit{units[1]}.bp() * 2 + rank) * NH + Unit{units[1]}.arg()) * SK * 2;
      const uint32_t bar = bars + BAR_BANK * 8;
      if (elect_one()) mbar_arrive_expect_tx(bar, BANK_N * 4096);
      __nanosleep(BANK_DELAY);
#pragma unroll 1
      for (int i = 0; i < 2 * BANK_N; i++) {
        const int tile = BANK_FIRST + (i >> 1) * (16 - BANK_FIRST) / BANK_N;
        if (elect_one()) tma_2d(sbase + OFF_SINK, (i & 1) ? &maps.vline[br] : &maps.kline[br], 0, line0 + tile * 128, bar);
        __nanosleep(BANK_PACE);
      }
      mbar_wait_sleep(bar, 0);
    }
    __syncwarp();
  } else if (wg == 0) {
    asm volatile("setmaxnreg.inc.sync.aligned.u32 192;");
    ARing r{0, 0};
    uint32_t lph = 0, gph = 0;
    bool opend = false;
    const uint32_t st_off = (16 * warp + (lane & 15)) * 64 + (((lane >> 4) ^ ((lane & 7) >> 1)) << 4);
#pragma unroll 1
    for (int u = 0;; u++) {
      const Unit un{units[u]};
      const int ty = un.type();
      if (ty == U_END) break;
      const bool mc_next = un.mc_next();
      if (ty == U_HQ) {
        r.adv(4);
        if (mc_next) {
          mbar_wait(bars + BAR_GLAST * 8, gph);
          gph ^= 1;
        }
        continue;
      }
      const bool at = ty == U_AT;
      const int n = ty == U_OP ? 64 : 16;
      const int rot = at ? 0 : un.rot();
      float acc0[80], acc1[80];
      if (at && !un.prev_at()) r.adv(3);
      const bool at_end = at && !un.next_at();
      const uint32_t bfull = bars + (at ? BAR_PFULL - 2 : BAR_XFULL) * 8, bempty = bars + (at ? BAR_PEMPTY - 2 : BAR_XEMPTY) * 8;
      uint32_t x = at ? 2 : rot;
      auto mainloop = [&](auto tb) {
        constexpr int TB = decltype(tb)::value;
        constexpr int KB = TB ? 64 : 2;
        mbar_wait(bfull + x * 8, 0);
        mbar_wait(bars + BAR_FO * 8, 0);
        {
          const uint32_t baddr = sbase + OFF_B + (2 + x) * B_BLK;
          const uint64_t da = make_desc(sbase + r.slot * A_SLOT), db = TB ? make_desc_n(baddr) : make_desc(baddr);
          wgmma_fence();
          wgmma_160_init<1, TB>(acc0, da, db);
          wgmma_160_init<1, TB>(acc1, da + 512, db);
#pragma unroll
          for (int kk = 1; kk < 4; kk++) {
            wgmma_160<1, TB>(acc0, da + kk * 128, db + kk * KB);
            wgmma_160<1, TB>(acc1, da + 512 + kk * 128, db + kk * KB);
          }
          wgmma_commit();
        }
        if (TB && opend) {
          fence_async_smem();
          __syncwarp();
          mbar_arrive_n(1, bars + BAR_OSTORE * 8);
        }
#pragma unroll 1
        for (int s = 1; s < n; s++) {
          const uint32_t pslot = r.slot, px = x;
          r.adv((at_end && s >= 14) ? 1 : 2);
          x = at ? 2 + (s & 1) : x_block(s, rot);
          const uint32_t bpar = at ? (s >> 1) & 1 : x_parity(s, rot);
          const uint32_t afull = bars + (BAR_FO + (s & 7)) * 8;
          const bool okb = mbar_test(bfull + x * 8, bpar), oka = mbar_test(afull, (s >> 3) & 1);
          const uint32_t baddr = sbase + OFF_B + (2 + x) * B_BLK;
          const uint64_t da = make_desc(sbase + r.slot * A_SLOT), db = TB ? make_desc_n(baddr) : make_desc(baddr);
          wgmma_wait<0>();
          mbar_arrive_n(1, bempty + px * 8);
          release_a(bars, pslot, s + (at ? 3 : 2) < n ? !at : mc_next, peer, 2);
          if (!okb) mbar_wait(bfull + x * 8, bpar);
          if (!oka) mbar_wait(afull, (s >> 3) & 1);
          if (TB ? s == 64 - OP_S_FIRST : (s == 16 - QP_S_FIRST && un.next_at())) {
            mbar_wait(bars + BAR_GLAST * 8, gph);
            gph ^= 1;
          }
          wgmma_fence();
#pragma unroll
          for (int kk = 0; kk < 4; kk++) {
            wgmma_160<1, TB>(acc0, da + kk * 128, db + kk * KB);
            wgmma_160<1, TB>(acc1, da + 512 + kk * 128, db + kk * KB);
          }
          wgmma_commit();
        }
      };
      if (ty == U_QP) {
        mainloop(Int<0>{});
        wgmma_wait<0>();
        mbar_arrive_n(1, bempty + x * 8);
        release_a(bars, r.slot, mc_next, peer, 2);
        r.adv(2);
        mbar_wait(bars + BAR_XEMPTY * 8, 1);
        store_block_n(acc0, Q_SCALE, sbase + OFF_B + 2 * B_BLK + st_off);
        mbar_wait(bars + (BAR_XEMPTY + 1) * 8, 1);
        store_block_n(acc1, Q_SCALE, sbase + OFF_B + 3 * B_BLK + st_off);
        fence_async_smem();
        __syncwarp();
        mbar_arrive_n(2, bars + (BAR_QFULL + 1) * 8);
      } else {
        mainloop(Int<1>{});
        if (at) {
          const uint32_t blk = 2 * un.qbuf();
          mbar_wait(bars + BAR_LREADY * 8, lph);
          lph ^= 1;
          float* linv = reinterpret_cast<float*>(smem + OFF_LINV);
          bool bad = false;
          if (lane < 20) {
            const int qp = warp * 20 + lane;
            const float2* lsum = reinterpret_cast<const float2*>(smem + OFF_LSUM) + qp;
            float2 l = lsum[0];
#pragma unroll
            for (int w = 1; w < 8; w++) {
              const float2 v = lsum[w * (SQ / 2)];
              l.x += v.x;
              l.y += v.y;
            }
            bad = !(l.x >= 9.094947e-13f && l.x <= 1.0995116e12f && l.y >= 9.094947e-13f && l.y <= 1.0995116e12f);
            *reinterpret_cast<float2*>(linv + (qp & 3) * 40 + (qp >> 2) * 2) = make_float2(__fdividef(1.f, l.x), __fdividef(1.f, l.y));
          }
          uint32_t anybad;
          asm volatile("{\n.reg .pred p, q;\nsetp.ne.b32 p, %1, 0;\nbar.red.or.pred q, 1, 128, p;\nselp.b32 %0, 1, 0, q;\n}\n"
                       : "=r"(anybad) : "r"((uint32_t)bad) : "memory");
          const float4* lv = reinterpret_cast<const float4*>(linv + (lane & 3) * 40);
          float4 iv[10];
#pragma unroll
          for (int i = 0; i < EP_PRE; i++) iv[i] = lv[i];
          wgmma_wait<0>();
          mbar_arrive_n(1, bempty + x * 8);
          mbar_arrive_n(1, bars + BAR_PDONE * 8);
          release_a(bars, r.slot, mc_next, peer, 2);
          r.adv(at_end ? 1 : 2);
          if (!__any_sync(0xffffffffu, anybad)) {
            const uint32_t addr = sbase + OFF_B + blk * B_BLK + st_off;
#pragma unroll
            for (int j = 0; j < 10; j++) {
              stsm_x4(n_addr(addr, j), pack_bf16(acc0[8 * j] * iv[j].x, acc0[8 * j + 1] * iv[j].y),
                      pack_bf16(acc0[8 * j + 2] * iv[j].x, acc0[8 * j + 3] * iv[j].y),
                      pack_bf16(acc0[8 * j + 4] * iv[j].z, acc0[8 * j + 5] * iv[j].w),
                      pack_bf16(acc0[8 * j + 6] * iv[j].z, acc0[8 * j + 7] * iv[j].w));
              stsm_x4(n_addr(addr, j) + B_BLK, pack_bf16(acc1[8 * j] * iv[j].x, acc1[8 * j + 1] * iv[j].y),
                      pack_bf16(acc1[8 * j + 2] * iv[j].x, acc1[8 * j + 3] * iv[j].y),
                      pack_bf16(acc1[8 * j + 4] * iv[j].z, acc1[8 * j + 5] * iv[j].w),
                      pack_bf16(acc1[8 * j + 6] * iv[j].z, acc1[8 * j + 7] * iv[j].w));
              if (j + EP_PRE < 10) iv[j + EP_PRE] = lv[j + EP_PRE];
            }
          } else {
            const size_t off = (size_t)((un.bp() * 2 + rank) * NH + un.arg()) * SK * DH;
            slow_attention(smem + OFF_B + blk * B_BLK, ptrs.k[br] + off, ptrs.v[br] + off, warp, lane);
          }
          opend = un.next_at();
          if (!opend) {
            fence_async_smem();
            __syncwarp();
            mbar_arrive_n(1, bars + BAR_OSTORE * 8);
          }
        } else {
          wgmma_wait<0>();
          mbar_arrive_n(1, bempty + x * 8);
          mbar_wait(bars + BAR_XEMPTY * 8, 1);
          store_block_t(acc0, sbase + OFF_B + 2 * B_BLK, warp, lane);
          mbar_wait(bars + (BAR_XEMPTY + 1) * 8, 1);
          store_block_t(acc1, sbase + OFF_B + 3 * B_BLK, warp, lane);
          fence_async_smem();
          __syncwarp();
          mbar_arrive_n(2, bars + (BAR_QFULL + 1) * 8);
        }
      }
    }
  } else {
    asm volatile("setmaxnreg.inc.sync.aligned.u32 144;");
    const int si = wg - 1;
    ARing r{0, 0};
    uint32_t qm = 0;
    const uint32_t st_off = (16 * warp + (lane & 15)) * 64 + (((lane >> 4) ^ ((lane & 7) >> 1)) << 4);
#pragma unroll 1
    for (int u = 0;; u++) {
      const Unit un{units[u]};
      const int ty = un.type();
      if (ty == U_END) break;
      const bool mc_next = un.mc_next();
      if (ty == U_AT) {
        const uint32_t qb = un.qbuf();
        if (un.qloaded()) qm ^= 1u << qb;
        mbar_wait(bars + (BAR_QFULL + qb) * 8, ((qm >> qb) & 1) ^ 1);
        const uint64_t dq = make_desc_n(sbase + OFF_B + 2 * qb * B_BLK);
        const uint32_t paddr = sbase + OFF_B + (4 + si) * B_BLK + st_off;
        uint32_t paddr1 = paddr ^ 32;
        asm volatile("" : "+r"(paddr1));
        float l[40];
#pragma unroll
        for (int i = 0; i < 40; i++) l[i] = 0.f;
        if (!un.prev_at()) r.adv(si);
        bool kok = false;
        if (si == 1 && !un.prev_at()) {
          const uint32_t c0 = clock();
          while ((uint32_t)clock() - c0 < COLD_STAGGER) {}
        }
        float* lsum = reinterpret_cast<float*>(smem + OFF_LSUM) + (si * 4 + warp) * SQ + (lane & 24) + 2 * (lane & 3) + ((lane >> 2) & 1);
        auto tile = [&](const int t, auto last) {
          constexpr bool LAST = decltype(last)::value;
          float acc[80];
          if (!kok) mbar_wait(bars + (BAR_FS + si + 2 * (t & 1)) * 8, (t >> 1) & 1);
          const uint64_t dk = make_desc(sbase + r.slot * A_SLOT);
          wgmma_fence();
          wgmma_160_init<0, 1>(acc, dk, dq);
#pragma unroll
          for (int kk = 1; kk < 8; kk++)
            wgmma_160<0, 1>(acc, dk + (kk >> 2) * 512 + (kk & 3) * 2, dq + (kk >> 2) * (B_BLK / 16) + (kk & 3) * 64);
          wgmma_commit();
          mbar_arrive_n(kok ? 1u : 0u, bars + (BAR_PFULL + si) * 8);
          wgmma_wait<0>();
          release_a(bars, r.slot, LAST ? mc_next : false, peer, 2);
          r.adv((t == 0 && !un.prev_at()) ? 2 + si : ((LAST && !un.next_at()) ? 6 - 2 * si : 4));
          auto expo = [&](int j) {
#pragma unroll
            for (int i = 0; i < 8; i++) acc[8 * j + i] = ex2(acc[8 * j + i]);
          };
          uint32_t pk[40];
          auto sums = [&](int c) {
            float* v = l + 8 * c;
            const bool h4 = lane & 16, h3 = lane & 8, h2 = lane & 4;
#pragma unroll
            for (int i = 0; i < 4; i++) v[i] = (h4 ? v[i + 4] : v[i]) + __shfl_xor_sync(0xffffffffu, h4 ? v[i] : v[i + 4], 16);
#pragma unroll
            for (int i = 0; i < 2; i++) v[i] = (h3 ? v[i + 2] : v[i]) + __shfl_xor_sync(0xffffffffu, h3 ? v[i] : v[i + 2], 8);
            lsum[32 * c] = (h2 ? v[1] : v[0]) + __shfl_xor_sync(0xffffffffu, h2 ? v[0] : v[1], 4);
          };
          auto reduce = [&](int j) {
            l[4 * j] += acc[8 * j] + acc[8 * j + 2];
            l[4 * j + 1] += acc[8 * j + 1] + acc[8 * j + 3];
            l[4 * j + 2] += acc[8 * j + 4] + acc[8 * j + 6];
            l[4 * j + 3] += acc[8 * j + 5] + acc[8 * j + 7];
#pragma unroll
            for (int i = 0; i < 4; i++) pk[4 * j + i] = pack_bf16(acc[8 * j + 2 * i], acc[8 * j + 2 * i + 1]);
            if (LAST && (j & 1) && j < 2 * L_EARLY) sums(j >> 1);
          };
          auto store = [&](int j) { stsm_x4((j & 1 ? paddr1 : paddr) + (j >> 1) * 4096, pk[4 * j], pk[4 * j + 1], pk[4 * j + 2], pk[4 * j + 3]); };
#pragma unroll
          for (int j = 0; j < SM_A; j++) expo(j);
          sched_fence(zero);
#pragma unroll
          for (int j = SM_A; j < SM_B; j++) expo(j);
#pragma unroll
          for (int j = 0; j < SM_A; j++) reduce(j);
          mbar_wait(bars + ((t == 0 && !un.prev_at() ? BAR_XEMPTY + 2 : BAR_PEMPTY) + si) * 8, (t & 1) ^ 1);
#pragma unroll
          for (int j = 0; j < SM_A; j++) store(j);
#pragma unroll
          for (int j = SM_B; j < 10; j++) expo(j);
#pragma unroll
          for (int j = SM_A; j < SM_B; j++) { reduce(j); store(j); }
          if (SM_B < 10) sched_fence(zero);
#pragma unroll
          for (int j = SM_B; j < 10; j++) { reduce(j); store(j); }
          kok = !LAST && mbar_test(bars + (BAR_FS + si + 2 * ((t + 1) & 1)) * 8, ((t + 1) >> 1) & 1);
          fence_async_smem();
          __syncwarp();
          mbar_arrive_n(kok ? 0u : 1u, bars + (BAR_PFULL + si) * 8);
          if (LAST) {
#pragma unroll
            for (int c = L_EARLY; c < 5; c++) sums(c);
            __syncwarp();
            mbar_arrive_n(1, bars + BAR_LREADY * 8);
          }
        };
#pragma unroll 1
        for (int t = 0; t < 7; t++) tile(t, Int<0>{});
        tile(7, Int<1>{});
      } else {
        float acc[80];
        const int n = ty == U_OP ? 64 : 16;
        const int rot = un.rot();
        const bool hq = ty == U_HQ;
        const uint32_t xcnt = hq ? 2 - si : 1, astep = hq ? 1 : 2;
        r.adv(astep - 1);
        uint32_t x = rot;
        auto mainloop = [&](auto tb) {
          constexpr int TB = decltype(tb)::value;
          constexpr int KB = TB ? 64 : 2;
          mbar_wait(bars + (BAR_XFULL + x) * 8, 0);
          mbar_wait(bars + ((hq && un.keep0()) ? BAR_FS : BAR_FG) * 8, 0);
          {
            const uint32_t baddr = sbase + OFF_B + (2 + x) * B_BLK;
            const uint64_t da = make_desc(sbase + r.slot * A_SLOT + si * 8192), db = TB ? make_desc_n(baddr) : make_desc(baddr);
            wgmma_fence();
            wgmma_160_init<1, TB>(acc, da, db);
#pragma unroll
            for (int kk = 1; kk < 4; kk++) wgmma_160<1, TB>(acc, da + kk * 128, db + kk * KB);
            wgmma_commit();
          }
#pragma unroll 1
          for (int s = 1; s < n; s++) {
            const uint32_t pslot = r.slot, px = x;
            r.adv(astep);
            x = x_block(s, rot);
            const uint32_t bpar = x_parity(s, rot);
            const uint32_t afull = bars + (((hq && !(s & 4) == un.keep0()) ? BAR_FS : BAR_FG) + (s & 3)) * 8, apar = (s >> (hq ? 3 : 2)) & 1;
            const bool okb = mbar_test(bars + (BAR_XFULL + x) * 8, bpar), oka = mbar_test(afull, apar);
            const uint32_t baddr = sbase + OFF_B + (2 + x) * B_BLK;
            const uint64_t da = make_desc(sbase + r.slot * A_SLOT + si * 8192), db = TB ? make_desc_n(baddr) : make_desc(baddr);
            wgmma_wait<0>();
            mbar_arrive_n(xcnt, bars + (BAR_XEMPTY + px) * 8);
            release_a(bars, pslot, astep * s - 1 + NA < astep * n ? true : mc_next, peer, 1);
            if (!okb) mbar_wait(bars + (BAR_XFULL + x) * 8, bpar);
            if (!oka) mbar_wait(afull, apar);
            wgmma_fence();
#pragma unroll
            for (int kk = 0; kk < 4; kk++) wgmma_160<1, TB>(acc, da + kk * 128, db + kk * KB);
            wgmma_commit();
          }
          mbar_arrive_n((TB || (hq ? mc_next : un.next_at())) ? 1u : 0u, bars + BAR_GLAST * 8);
          wgmma_wait<0>();
          mbar_arrive_n(xcnt, bars + (BAR_XEMPTY + x) * 8);
          release_a(bars, r.slot, mc_next, peer, 1);
          r.adv(1);
          mbar_wait(bars + BAR_QEMPTY * 8, (qm & 1) ^ 1);
        };
        if (ty != U_OP) {
          mainloop(Int<0>{});
          store_block_n(acc, Q_SCALE, sbase + OFF_B + si * B_BLK + st_off);
        } else {
          mainloop(Int<1>{});
          store_block_t(acc, sbase + OFF_B + si * B_BLK, warp, lane);
        }
        fence_async_smem();
        __syncwarp();
        mbar_arrive_n(1, bars + BAR_QFULL * 8);
        qm ^= hq ? 1 : 3;
      }
    }
  }
}

typedef CUresult (*EncodeFn)(CUtensorMap*, CUtensorMapDataType, cuuint32_t, void*, const cuuint64_t*, const cuuint64_t*,
                             const cuuint32_t*, const cuuint32_t*, CUtensorMapInterleave, CUtensorMapSwizzle,
                             CUtensorMapL2promotion, CUtensorMapFloatOOBfill);

void make_map_2d(EncodeFn enc, CUtensorMap* m, const void* p, uint64_t cols, uint64_t rows, uint32_t box_rows) {
  cuuint64_t dims[2] = {cols, rows}, strides[1] = {cols * 2};
  cuuint32_t box[2] = {64, box_rows}, es[2] = {1, 1};
  enc(m, CU_TENSOR_MAP_DATA_TYPE_BFLOAT16, 2, const_cast<void*>(p), dims, strides, box, es, CU_TENSOR_MAP_INTERLEAVE_NONE,
      CU_TENSOR_MAP_SWIZZLE_128B, CU_TENSOR_MAP_L2_PROMOTION_L2_128B, CU_TENSOR_MAP_FLOAT_OOB_FILL_NONE);
}
void make_map_kv(EncodeFn enc, CUtensorMap* m, const void* p) {
  cuuint64_t dims[3] = {64, (cuuint64_t)NB * NH * SK, 2}, strides[2] = {DH * 2, 128};
  cuuint32_t box[3] = {64, 64, 2}, es[3] = {1, 1, 1};
  enc(m, CU_TENSOR_MAP_DATA_TYPE_BFLOAT16, 3, const_cast<void*>(p), dims, strides, box, es, CU_TENSOR_MAP_INTERLEAVE_NONE,
      CU_TENSOR_MAP_SWIZZLE_128B, CU_TENSOR_MAP_L2_PROMOTION_L2_128B, CU_TENSOR_MAP_FLOAT_OOB_FILL_NONE);
}

void make_map_lines(EncodeFn enc, CUtensorMap* m, const void* p) {
  cuuint64_t dims[2] = {64, (cuuint64_t)NB * NH * SK * 2}, strides[1] = {128};
  cuuint32_t box[2] = {8, 128}, es[2] = {1, 1};
  enc(m, CU_TENSOR_MAP_DATA_TYPE_BFLOAT16, 2, const_cast<void*>(p), dims, strides, box, es, CU_TENSOR_MAP_INTERLEAVE_NONE,
      CU_TENSOR_MAP_SWIZZLE_NONE, CU_TENSOR_MAP_L2_PROMOTION_L2_128B, CU_TENSOR_MAP_FLOAT_OOB_FILL_NONE);
}

void make_plan(Plan* p, bool spare) {
  enum { F_QBUF1 = 1 << 10, F_LOAD = 1 << 11, F_KEEP0 = 1 << 12, F_BANK = 1 << 13, F_KEEP1 = 1 << 17 };
  const char* with_spare[9] = {"qqqqo", "haaaaaaa", "qqQao", "haaaaaaa", "hbxqqo", "Kaaaaaaa", "hbxqqo", "Kaaaaaaa", "a"};
  const char* without[9] = {"qqQaxo", "haaaaaaa", "qqQaxo", "haaaaaaa", "hbqqqo", "haaaaaaa", "hbqqqo", "haaaaaaa", ""};
  const char* const* prog = spare ? with_spare : without;
  const int delay_spare[9][MAX_UNITS] = {{8, 0, 0, 36}, {0, 0, 0, 0, 24}, {34, 0, 0, 16}, {7}, {0, 16, 0, 16, 28}, {},
                                         {0, 0, 0, 24, 28}, {}, {280}};
  const int delay_without[9][MAX_UNITS] = {{}, {}, {}, {10}, {}, {20}, {}, {30}, {}};
  const int (*delay)[MAX_UNITS] = spare ? delay_spare : delay_without;
  struct Slot { float t; int a, b; };
  Slot supply[NH], demand[NH];
  int ns = 0, nd = 0, next_pair = 0, next_single = NH - 1;
  int type[9][MAX_UNITS], arg[9][MAX_UNITS], flags[9][MAX_UNITS], len[9];
  float tend[9][MAX_UNITS];
  for (int k = 0; k < MAX_UNITS; k++)
    for (int r = 0; r < 9; r++) {
      if (k == 0) len[r] = (int)strlen(prog[r]);
      if (k >= len[r]) continue;
      const char c = prog[r][k];
      const float t0 = (k ? tend[r][k - 1] : 0.f) + delay[r][k] / 88.f;
      tend[r][k] = t0 + ((c == 'h' || c == 'x') ? 0.6f : 1.f);
      flags[r][k] = delay[r][k] << 20;
      if (c == 'q' || c == 'Q' || c == 'K') {
        type[r][k] = U_QP;
        arg[r][k] = next_pair++;
        flags[r][k] |= (c != 'q' ? F_KEEP0 : 0) | (c == 'K' ? F_KEEP1 : 0);
        if (c == 'q') supply[ns++] = {tend[r][k], 2 * arg[r][k], 0};
        if (c != 'K') supply[ns++] = {tend[r][k], 2 * arg[r][k] + 1, 0};
      } else if (c == 'h' || c == 'x') {
        type[r][k] = U_HQ;
        arg[r][k] = next_single--;
        if (c == 'h') flags[r][k] |= F_KEEP0;
        else supply[ns++] = {tend[r][k], arg[r][k], 0};
      } else if (c == 'o') {
        type[r][k] = U_OP;
        arg[r][k] = r >> 1;
      } else {
        type[r][k] = U_AT;
        const char p1 = k > 0 ? prog[r][k - 1] : 0, p2 = k > 1 ? prog[r][k - 2] : 0;
        if (k > 0 && type[r][k - 1] == U_AT && !(flags[r][k - 1] & F_QBUF1)) flags[r][k] |= F_QBUF1;
        if (c == 'b') flags[r][k] |= F_BANK;
        if (p1 == 'h') arg[r][k] = arg[r][k - 1];
        else if (p1 == 'Q' || p1 == 'K') arg[r][k] = 2 * arg[r][k - 1];
        else if (p2 == 'K') arg[r][k] = 2 * arg[r][k - 2] + 1;
        else { flags[r][k] |= F_LOAD; demand[nd++] = {t0, r, k}; }
      }
    }
  auto earlier = [](const Slot& x, const Slot& y) { return x.t < y.t; };
  std::stable_sort(supply, supply + ns, earlier);
  std::stable_sort(demand, demand + nd, earlier);
  for (int i = 0; i < nd; i++) arg[demand[i].a][demand[i].b] = supply[i].a;
  Slot done[NH];
  int ndone = 0;
  for (int role = 0; role < MAX_ROLES; role++) {
    const int r = role == 32 ? 8 : role & 7, n = role == 32 ? 4 * len[8] : len[r];
    for (int k = 0; k < MAX_UNITS; k++) {
      if (k >= n) { p->unit[role][k] = U_END; continue; }
      const int kk = role == 32 ? 0 : k;
      uint32_t d = type[r][kk] | (arg[r][kk] << 3) | ((role == 32 ? k : role >> 3) << 8) | flags[r][kk];
      if (role == 32 && k > 0) d = (d & 0xFFFFFu) | ((k & 1) ? F_QBUF1 : 0);
      const int prev = k == 0 ? U_END : type[r][role == 32 ? 0 : k - 1], next = k + 1 == n ? U_END : type[r][role == 32 ? 0 : k + 1];
      if (type[r][kk] != U_AT && prev == U_QP) d |= 1u << 14;
      if (prev == U_AT) d |= 1u << 15;
      if (next != U_END) d |= 1u << (next != U_AT ? 16 : 18);
      p->unit[role][k] = d;
      if (type[r][kk] == U_AT && (role < 8 || (role == 32 && k == 3))) done[ndone++] = {tend[r][kk] + (role == 32 ? 3.f : 0.f), arg[r][kk], 0};
    }
  }
  std::stable_sort(done, done + NH, earlier);
  for (int i = 0; i < NH; i++) p->op_head[i] = (uint8_t)done[i].a;
}

}

extern "C" void kernel_launch(void* const* d_in, const int* in_sizes, int n_in, void* d_out, int out_size) {
  (void)in_sizes; (void)n_in; (void)out_size;
  void* fn = nullptr;
  cudaDriverEntryPointQueryResult qr;
  cudaGetDriverEntryPoint("cuTensorMapEncodeTiled", &fn, cudaEnableDefault, &qr);
  EncodeFn enc = reinterpret_cast<EncodeFn>(fn);
  Maps maps;
  Ptrs ptrs;
  for (int br = 0; br < 2; br++) {
    void* const* in = d_in + 5 * br;
    make_map_2d(enc, &maps.x[br], in[0], DM, NB * SQ, SQ);
    make_map_kv(enc, &maps.k[br], in[1]);
    make_map_kv(enc, &maps.v[br], in[2]);
    make_map_lines(enc, &maps.kline[br], in[1]);
    make_map_lines(enc, &maps.vline[br], in[2]);
    make_map_2d(enc, &maps.wq[br], in[3], NH * DH, DM, 64);
    make_map_2d(enc, &maps.wo[br], in[4], DM, NH * DH, 64);
    ptrs.k[br] = static_cast<const __nv_bfloat16*>(in[1]);
    ptrs.v[br] = static_cast<const __nv_bfloat16*>(in[2]);
  }
  void* sym = nullptr;
  cudaGetSymbolAddress(&sym, g_scratch);
  ptrs.scratch = reinterpret_cast<uint8_t*>((reinterpret_cast<uintptr_t>(sym) + PAGE - 1) & ~(uintptr_t)(PAGE - 1));
  make_map_2d(enc, &maps.out, d_out, 2 * DM, NB * SQ, SQ);
  cudaFuncSetAttribute(mha2_kernel, cudaFuncAttributeMaxDynamicSharedMemorySize, SMEM_BYTES);
  cudaLaunchConfig_t cfg = {};
  cfg.gridDim = 132;
  cfg.blockDim = 512;
  cfg.dynamicSmemBytes = SMEM_BYTES;
  int ncl = 0;
  cudaOccupancyMaxActiveClusters(&ncl, mha2_kernel, &cfg);
  ncl = ncl >= 66 ? 66 : 64;
  Plan plan;
  make_plan(&plan, ncl == 66);
  mha2_kernel<<<2 * ncl, 512, SMEM_BYTES, cudaStreamPerThread>>>(ptrs, plan, maps);
}
```
